```python
import torch

def _softmax(x, axis=-1):
    return torch.softmax(x, dim=axis)
def _gelu(x):
    return torch.nn.functional.gelu(x, approximate="tanh")
def _silu(x):
    return torch.nn.functional.silu(x)
def _sigmoid(x):
    return torch.sigmoid(x)
def _layernorm(x, axis=-1, eps=1e-5):
    m = x.mean(dim=axis, keepdim=True)
    v = x.var(dim=axis, keepdim=True, unbiased=False)
    return (x - m) / torch.sqrt(v + eps)
def _scatter_add(tgt, idx, src, axis=0):
    return tgt.clone().index_add_(axis, idx, src)
def _segment_sum(src, seg, n):
    out = torch.zeros((n,) + src.shape[1:], dtype=src.dtype)
    return out.index_add_(0, seg, src)
def _pad(x, pw):
    flat = tuple(v for pair in reversed(pw) for v in pair)
    return torch.nn.functional.pad(x, flat)

kernel_name = 'recurrent_scan__linear_kernel_hedgehog__dense_activation_gelu__prompt'

def setup_inputs():

    _w = (lambda a: (lambda t: t.to(torch.bfloat16) if t.is_floating_point() else t)(torch.as_tensor(a)))
    def _A_setup():
        B, S, D, H = 1, 2048, 1024, 32
        Dh = D // H
        return {
            "x": _w((lambda *s: torch.randn(*s, dtype=torch.bfloat16) * 0.05)(B, S, D)),
            "wqkv": _w((lambda *s: torch.randn(*s, dtype=torch.bfloat16) * 0.4)(D, 3 * D)),
            "w_phi": _w((lambda *s: torch.randn(*s, dtype=torch.bfloat16) * 0.4)(H, Dh, Dh) * (Dh ** -0.5)),
            "wo": _w((lambda *s: torch.randn(*s, dtype=torch.bfloat16) * 0.2)(D, D)),
        }
    _A_in = _A_setup()

    def _B_setup():
        B, S, D, F = 1, 2048, 1024, 3584
        return {
            "x": _w((lambda *s: torch.randn(*s, dtype=torch.bfloat16) * 0.05)(B, S, D)),
            "w1": _w((lambda *s: torch.randn(*s, dtype=torch.bfloat16) * 0.4)(D, F) * (D ** -0.5)),
            "b1": _w((lambda *s: torch.randn(*s, dtype=torch.bfloat16) * 12.8)(F) * 0.01),
            "w2": _w((lambda *s: torch.randn(*s, dtype=torch.bfloat16) * 0.1)(F, D) * (F ** -0.5)),
            "b2": _w((lambda *s: torch.randn(*s, dtype=torch.bfloat16) * 0.8)(D) * 0.01),
        }
    _B_in = _B_setup()

    return {
        "A_x": _A_in["x"],
        "A_wqkv": _A_in["wqkv"],
        "A_w_phi": _A_in["w_phi"],
        "A_wo": _A_in["wo"],
        "B_x": _B_in["x"],
        "B_w1": _B_in["w1"],
        "B_b1": _B_in["b1"],
        "B_w2": _B_in["w2"],
        "B_b2": _B_in["b2"],
    }

def reference(A_x, A_wqkv, A_w_phi, A_wo, B_x, B_w1, B_b1, B_w2, B_b2):
    def _A_ref(x, wqkv, w_phi, wo):
        B, S, D = x.shape
        H = 32; Dh = D // H
        qkv = (lambda x, *d: x.permute(*d))((x @ wqkv).reshape(B, S, 3, H, Dh), 2, 0, 3, 1, 4)
        q, k, v = qkv[0], qkv[1], qkv[2]
        pq = torch.einsum("bhsd,hdf->bhsf", q, w_phi)
        pk = torch.einsum("bhsd,hdf->bhsf", k, w_phi)
        phi_q = torch.concatenate([_softmax(pq, axis=-1), _softmax(-pq, axis=-1)], axis=-1)
        phi_k = torch.concatenate([_softmax(pk, axis=-1), _softmax(-pk, axis=-1)], axis=-1)
        kv = torch.einsum("bhsf,bhsd->bhfd", phi_k, v)
        z  = torch.einsum("bhsf->bhf", phi_k)
        num = torch.einsum("bhqf,bhfd->bhqd", phi_q, kv)
        den = torch.einsum("bhqf,bhf->bhq", phi_q, z)[..., None] + 1e-6
        o = num / den
        return (lambda x, *d: x.permute(*d))(o, 0, 2, 1, 3).reshape(B, S, D) @ wo

    def _B_ref(x, w1, b1, w2, b2):
        h = torch.einsum("bsd,df->bsf", x, w1) + b1
        h = _gelu(h)
        return torch.einsum("bsf,fd->bsd", h, w2) + b2

    x = A_x
    xn = _layernorm(x, axis=-1)
    s = _A_ref(xn, A_wqkv, A_w_phi, A_wo)
    g = _silu(_B_ref(xn, B_w1, B_b1, B_w2, B_b2))
    return x + s * g
```

```cpp
#include <cuda_runtime.h>
#include <cuda_bf16.h>
#include <cuda.h>
#include <stdint.h>

namespace {

typedef __nv_bfloat16 bf16;

template<int TA, int TB> __device__ __forceinline__ void wgmma_ss256_p(float* d, uint64_t da, uint64_t db, int sd) {
  asm volatile("{\n.reg .pred p;\nsetp.ne.b32 p, %130, 0;\nwgmma.mma_async.sync.aligned.m64n256k16.f32.bf16.bf16 "
    "{%0, %1, %2, %3, %4, %5, %6, %7, %8, %9, %10, %11, %12, %13, %14, %15, %16, %17, %18, %19, %20, %21, %22, %23, %24, %25, %26, %27, %28, %29, %30, %31, %32, %33, %34, %35, %36, %37, %38, %39, %40, %41, %42, %43, %44, %45, %46, %47, %48, %49, %50, %51, %52, %53, %54, %55, %56, %57, %58, %59, %60, %61, %62, %63, %64, %65, %66, %67, %68, %69, %70, %71, %72, %73, %74, %75, %76, %77, %78, %79, %80, %81, %82, %83, %84, %85, %86, %87, %88, %89, %90, %91, %92, %93, %94, %95, %96, %97, %98, %99, %100, %101, %102, %103, %104, %105, %106, %107, %108, %109, %110, %111, %112, %113, %114, %115, %116, %117, %118, %119, %120, %121, %122, %123, %124, %125, %126, %127}, %128, %129, p, 1, 1, %131, %132;\n}"
    : "+f"(d[0]), "+f"(d[1]), "+f"(d[2]), "+f"(d[3]), "+f"(d[4]), "+f"(d[5]), "+f"(d[6]), "+f"(d[7]), "+f"(d[8]), "+f"(d[9]), "+f"(d[10]), "+f"(d[11]), "+f"(d[12]), "+f"(d[13]), "+f"(d[14]), "+f"(d[15]), "+f"(d[16]), "+f"(d[17]), "+f"(d[18]), "+f"(d[19]), "+f"(d[20]), "+f"(d[21]), "+f"(d[22]), "+f"(d[23]), "+f"(d[24]), "+f"(d[25]), "+f"(d[26]), "+f"(d[27]), "+f"(d[28]), "+f"(d[29]), "+f"(d[30]), "+f"(d[31]), "+f"(d[32]), "+f"(d[33]), "+f"(d[34]), "+f"(d[35]), "+f"(d[36]), "+f"(d[37]), "+f"(d[38]), "+f"(d[39]), "+f"(d[40]), "+f"(d[41]), "+f"(d[42]), "+f"(d[43]), "+f"(d[44]), "+f"(d[45]), "+f"(d[46]), "+f"(d[47]), "+f"(d[48]), "+f"(d[49]), "+f"(d[50]), "+f"(d[51]), "+f"(d[52]), "+f"(d[53]), "+f"(d[54]), "+f"(d[55]), "+f"(d[56]), "+f"(d[57]), "+f"(d[58]), "+f"(d[59]), "+f"(d[60]), "+f"(d[61]), "+f"(d[62]), "+f"(d[63]), "+f"(d[64]), "+f"(d[65]), "+f"(d[66]), "+f"(d[67]), "+f"(d[68]), "+f"(d[69]), "+f"(d[70]), "+f"(d[71]), "+f"(d[72]), "+f"(d[73]), "+f"(d[74]), "+f"(d[75]), "+f"(d[76]), "+f"(d[77]), "+f"(d[78]), "+f"(d[79]), "+f"(d[80]), "+f"(d[81]), "+f"(d[82]), "+f"(d[83]), "+f"(d[84]), "+f"(d[85]), "+f"(d[86]), "+f"(d[87]), "+f"(d[88]), "+f"(d[89]), "+f"(d[90]), "+f"(d[91]), "+f"(d[92]), "+f"(d[93]), "+f"(d[94]), "+f"(d[95]), "+f"(d[96]), "+f"(d[97]), "+f"(d[98]), "+f"(d[99]), "+f"(d[100]), "+f"(d[101]), "+f"(d[102]), "+f"(d[103]), "+f"(d[104]), "+f"(d[105]), "+f"(d[106]), "+f"(d[107]), "+f"(d[108]), "+f"(d[109]), "+f"(d[110]), "+f"(d[111]), "+f"(d[112]), "+f"(d[113]), "+f"(d[114]), "+f"(d[115]), "+f"(d[116]), "+f"(d[117]), "+f"(d[118]), "+f"(d[119]), "+f"(d[120]), "+f"(d[121]), "+f"(d[122]), "+f"(d[123]), "+f"(d[124]), "+f"(d[125]), "+f"(d[126]), "+f"(d[127])
    : "l"(da), "l"(db), "r"(sd), "n"(TA), "n"(TB));
}
template<int TA, int TB> __device__ __forceinline__ void wgmma_ss256(float* d, uint64_t da, uint64_t db) {
  asm volatile("wgmma.mma_async.sync.aligned.m64n256k16.f32.bf16.bf16 "
    "{%0, %1, %2, %3, %4, %5, %6, %7, %8, %9, %10, %11, %12, %13, %14, %15, %16, %17, %18, %19, %20, %21, %22, %23, %24, %25, %26, %27, %28, %29, %30, %31, %32, %33, %34, %35, %36, %37, %38, %39, %40, %41, %42, %43, %44, %45, %46, %47, %48, %49, %50, %51, %52, %53, %54, %55, %56, %57, %58, %59, %60, %61, %62, %63, %64, %65, %66, %67, %68, %69, %70, %71, %72, %73, %74, %75, %76, %77, %78, %79, %80, %81, %82, %83, %84, %85, %86, %87, %88, %89, %90, %91, %92, %93, %94, %95, %96, %97, %98, %99, %100, %101, %102, %103, %104, %105, %106, %107, %108, %109, %110, %111, %112, %113, %114, %115, %116, %117, %118, %119, %120, %121, %122, %123, %124, %125, %126, %127}, %128, %129, 1, 1, 1, %130, %131;"
    : "+f"(d[0]), "+f"(d[1]), "+f"(d[2]), "+f"(d[3]), "+f"(d[4]), "+f"(d[5]), "+f"(d[6]), "+f"(d[7]), "+f"(d[8]), "+f"(d[9]), "+f"(d[10]), "+f"(d[11]), "+f"(d[12]), "+f"(d[13]), "+f"(d[14]), "+f"(d[15]), "+f"(d[16]), "+f"(d[17]), "+f"(d[18]), "+f"(d[19]), "+f"(d[20]), "+f"(d[21]), "+f"(d[22]), "+f"(d[23]), "+f"(d[24]), "+f"(d[25]), "+f"(d[26]), "+f"(d[27]), "+f"(d[28]), "+f"(d[29]), "+f"(d[30]), "+f"(d[31]), "+f"(d[32]), "+f"(d[33]), "+f"(d[34]), "+f"(d[35]), "+f"(d[36]), "+f"(d[37]), "+f"(d[38]), "+f"(d[39]), "+f"(d[40]), "+f"(d[41]), "+f"(d[42]), "+f"(d[43]), "+f"(d[44]), "+f"(d[45]), "+f"(d[46]), "+f"(d[47]), "+f"(d[48]), "+f"(d[49]), "+f"(d[50]), "+f"(d[51]), "+f"(d[52]), "+f"(d[53]), "+f"(d[54]), "+f"(d[55]), "+f"(d[56]), "+f"(d[57]), "+f"(d[58]), "+f"(d[59]), "+f"(d[60]), "+f"(d[61]), "+f"(d[62]), "+f"(d[63]), "+f"(d[64]), "+f"(d[65]), "+f"(d[66]), "+f"(d[67]), "+f"(d[68]), "+f"(d[69]), "+f"(d[70]), "+f"(d[71]), "+f"(d[72]), "+f"(d[73]), "+f"(d[74]), "+f"(d[75]), "+f"(d[76]), "+f"(d[77]), "+f"(d[78]), "+f"(d[79]), "+f"(d[80]), "+f"(d[81]), "+f"(d[82]), "+f"(d[83]), "+f"(d[84]), "+f"(d[85]), "+f"(d[86]), "+f"(d[87]), "+f"(d[88]), "+f"(d[89]), "+f"(d[90]), "+f"(d[91]), "+f"(d[92]), "+f"(d[93]), "+f"(d[94]), "+f"(d[95]), "+f"(d[96]), "+f"(d[97]), "+f"(d[98]), "+f"(d[99]), "+f"(d[100]), "+f"(d[101]), "+f"(d[102]), "+f"(d[103]), "+f"(d[104]), "+f"(d[105]), "+f"(d[106]), "+f"(d[107]), "+f"(d[108]), "+f"(d[109]), "+f"(d[110]), "+f"(d[111]), "+f"(d[112]), "+f"(d[113]), "+f"(d[114]), "+f"(d[115]), "+f"(d[116]), "+f"(d[117]), "+f"(d[118]), "+f"(d[119]), "+f"(d[120]), "+f"(d[121]), "+f"(d[122]), "+f"(d[123]), "+f"(d[124]), "+f"(d[125]), "+f"(d[126]), "+f"(d[127])
    : "l"(da), "l"(db), "n"(TA), "n"(TB));
}
template<int TA, int TB> __device__ __forceinline__ void wgmma_ss192_p(float* d, uint64_t da, uint64_t db, int sd) {
  asm volatile("{\n.reg .pred p;\nsetp.ne.b32 p, %98, 0;\nwgmma.mma_async.sync.aligned.m64n192k16.f32.bf16.bf16 "
    "{%0, %1, %2, %3, %4, %5, %6, %7, %8, %9, %10, %11, %12, %13, %14, %15, %16, %17, %18, %19, %20, %21, %22, %23, %24, %25, %26, %27, %28, %29, %30, %31, %32, %33, %34, %35, %36, %37, %38, %39, %40, %41, %42, %43, %44, %45, %46, %47, %48, %49, %50, %51, %52, %53, %54, %55, %56, %57, %58, %59, %60, %61, %62, %63, %64, %65, %66, %67, %68, %69, %70, %71, %72, %73, %74, %75, %76, %77, %78, %79, %80, %81, %82, %83, %84, %85, %86, %87, %88, %89, %90, %91, %92, %93, %94, %95}, %96, %97, p, 1, 1, %99, %100;\n}"
    : "+f"(d[0]), "+f"(d[1]), "+f"(d[2]), "+f"(d[3]), "+f"(d[4]), "+f"(d[5]), "+f"(d[6]), "+f"(d[7]), "+f"(d[8]), "+f"(d[9]), "+f"(d[10]), "+f"(d[11]), "+f"(d[12]), "+f"(d[13]), "+f"(d[14]), "+f"(d[15]), "+f"(d[16]), "+f"(d[17]), "+f"(d[18]), "+f"(d[19]), "+f"(d[20]), "+f"(d[21]), "+f"(d[22]), "+f"(d[23]), "+f"(d[24]), "+f"(d[25]), "+f"(d[26]), "+f"(d[27]), "+f"(d[28]), "+f"(d[29]), "+f"(d[30]), "+f"(d[31]), "+f"(d[32]), "+f"(d[33]), "+f"(d[34]), "+f"(d[35]), "+f"(d[36]), "+f"(d[37]), "+f"(d[38]), "+f"(d[39]), "+f"(d[40]), "+f"(d[41]), "+f"(d[42]), "+f"(d[43]), "+f"(d[44]), "+f"(d[45]), "+f"(d[46]), "+f"(d[47]), "+f"(d[48]), "+f"(d[49]), "+f"(d[50]), "+f"(d[51]), "+f"(d[52]), "+f"(d[53]), "+f"(d[54]), "+f"(d[55]), "+f"(d[56]), "+f"(d[57]), "+f"(d[58]), "+f"(d[59]), "+f"(d[60]), "+f"(d[61]), "+f"(d[62]), "+f"(d[63]), "+f"(d[64]), "+f"(d[65]), "+f"(d[66]), "+f"(d[67]), "+f"(d[68]), "+f"(d[69]), "+f"(d[70]), "+f"(d[71]), "+f"(d[72]), "+f"(d[73]), "+f"(d[74]), "+f"(d[75]), "+f"(d[76]), "+f"(d[77]), "+f"(d[78]), "+f"(d[79]), "+f"(d[80]), "+f"(d[81]), "+f"(d[82]), "+f"(d[83]), "+f"(d[84]), "+f"(d[85]), "+f"(d[86]), "+f"(d[87]), "+f"(d[88]), "+f"(d[89]), "+f"(d[90]), "+f"(d[91]), "+f"(d[92]), "+f"(d[93]), "+f"(d[94]), "+f"(d[95])
    : "l"(da), "l"(db), "r"(sd), "n"(TA), "n"(TB));
}
template<int TA, int TB> __device__ __forceinline__ void wgmma_ss192(float* d, uint64_t da, uint64_t db) {
  asm volatile("wgmma.mma_async.sync.aligned.m64n192k16.f32.bf16.bf16 "
    "{%0, %1, %2, %3, %4, %5, %6, %7, %8, %9, %10, %11, %12, %13, %14, %15, %16, %17, %18, %19, %20, %21, %22, %23, %24, %25, %26, %27, %28, %29, %30, %31, %32, %33, %34, %35, %36, %37, %38, %39, %40, %41, %42, %43, %44, %45, %46, %47, %48, %49, %50, %51, %52, %53, %54, %55, %56, %57, %58, %59, %60, %61, %62, %63, %64, %65, %66, %67, %68, %69, %70, %71, %72, %73, %74, %75, %76, %77, %78, %79, %80, %81, %82, %83, %84, %85, %86, %87, %88, %89, %90, %91, %92, %93, %94, %95}, %96, %97, 1, 1, 1, %98, %99;"
    : "+f"(d[0]), "+f"(d[1]), "+f"(d[2]), "+f"(d[3]), "+f"(d[4]), "+f"(d[5]), "+f"(d[6]), "+f"(d[7]), "+f"(d[8]), "+f"(d[9]), "+f"(d[10]), "+f"(d[11]), "+f"(d[12]), "+f"(d[13]), "+f"(d[14]), "+f"(d[15]), "+f"(d[16]), "+f"(d[17]), "+f"(d[18]), "+f"(d[19]), "+f"(d[20]), "+f"(d[21]), "+f"(d[22]), "+f"(d[23]), "+f"(d[24]), "+f"(d[25]), "+f"(d[26]), "+f"(d[27]), "+f"(d[28]), "+f"(d[29]), "+f"(d[30]), "+f"(d[31]), "+f"(d[32]), "+f"(d[33]), "+f"(d[34]), "+f"(d[35]), "+f"(d[36]), "+f"(d[37]), "+f"(d[38]), "+f"(d[39]), "+f"(d[40]), "+f"(d[41]), "+f"(d[42]), "+f"(d[43]), "+f"(d[44]), "+f"(d[45]), "+f"(d[46]), "+f"(d[47]), "+f"(d[48]), "+f"(d[49]), "+f"(d[50]), "+f"(d[51]), "+f"(d[52]), "+f"(d[53]), "+f"(d[54]), "+f"(d[55]), "+f"(d[56]), "+f"(d[57]), "+f"(d[58]), "+f"(d[59]), "+f"(d[60]), "+f"(d[61]), "+f"(d[62]), "+f"(d[63]), "+f"(d[64]), "+f"(d[65]), "+f"(d[66]), "+f"(d[67]), "+f"(d[68]), "+f"(d[69]), "+f"(d[70]), "+f"(d[71]), "+f"(d[72]), "+f"(d[73]), "+f"(d[74]), "+f"(d[75]), "+f"(d[76]), "+f"(d[77]), "+f"(d[78]), "+f"(d[79]), "+f"(d[80]), "+f"(d[81]), "+f"(d[82]), "+f"(d[83]), "+f"(d[84]), "+f"(d[85]), "+f"(d[86]), "+f"(d[87]), "+f"(d[88]), "+f"(d[89]), "+f"(d[90]), "+f"(d[91]), "+f"(d[92]), "+f"(d[93]), "+f"(d[94]), "+f"(d[95])
    : "l"(da), "l"(db), "n"(TA), "n"(TB));
}
template<int TA, int TB> __device__ __forceinline__ void wgmma_ss128_p(float* d, uint64_t da, uint64_t db, int sd) {
  asm volatile("{\n.reg .pred p;\nsetp.ne.b32 p, %66, 0;\nwgmma.mma_async.sync.aligned.m64n128k16.f32.bf16.bf16 "
    "{%0, %1, %2, %3, %4, %5, %6, %7, %8, %9, %10, %11, %12, %13, %14, %15, %16, %17, %18, %19, %20, %21, %22, %23, %24, %25, %26, %27, %28, %29, %30, %31, %32, %33, %34, %35, %36, %37, %38, %39, %40, %41, %42, %43, %44, %45, %46, %47, %48, %49, %50, %51, %52, %53, %54, %55, %56, %57, %58, %59, %60, %61, %62, %63}, %64, %65, p, 1, 1, %67, %68;\n}"
    : "+f"(d[0]), "+f"(d[1]), "+f"(d[2]), "+f"(d[3]), "+f"(d[4]), "+f"(d[5]), "+f"(d[6]), "+f"(d[7]), "+f"(d[8]), "+f"(d[9]), "+f"(d[10]), "+f"(d[11]), "+f"(d[12]), "+f"(d[13]), "+f"(d[14]), "+f"(d[15]), "+f"(d[16]), "+f"(d[17]), "+f"(d[18]), "+f"(d[19]), "+f"(d[20]), "+f"(d[21]), "+f"(d[22]), "+f"(d[23]), "+f"(d[24]), "+f"(d[25]), "+f"(d[26]), "+f"(d[27]), "+f"(d[28]), "+f"(d[29]), "+f"(d[30]), "+f"(d[31]), "+f"(d[32]), "+f"(d[33]), "+f"(d[34]), "+f"(d[35]), "+f"(d[36]), "+f"(d[37]), "+f"(d[38]), "+f"(d[39]), "+f"(d[40]), "+f"(d[41]), "+f"(d[42]), "+f"(d[43]), "+f"(d[44]), "+f"(d[45]), "+f"(d[46]), "+f"(d[47]), "+f"(d[48]), "+f"(d[49]), "+f"(d[50]), "+f"(d[51]), "+f"(d[52]), "+f"(d[53]), "+f"(d[54]), "+f"(d[55]), "+f"(d[56]), "+f"(d[57]), "+f"(d[58]), "+f"(d[59]), "+f"(d[60]), "+f"(d[61]), "+f"(d[62]), "+f"(d[63])
    : "l"(da), "l"(db), "r"(sd), "n"(TA), "n"(TB));
}
template<int TA, int TB> __device__ __forceinline__ void wgmma_ss128(float* d, uint64_t da, uint64_t db) {
  asm volatile("wgmma.mma_async.sync.aligned.m64n128k16.f32.bf16.bf16 "
    "{%0, %1, %2, %3, %4, %5, %6, %7, %8, %9, %10, %11, %12, %13, %14, %15, %16, %17, %18, %19, %20, %21, %22, %23, %24, %25, %26, %27, %28, %29, %30, %31, %32, %33, %34, %35, %36, %37, %38, %39, %40, %41, %42, %43, %44, %45, %46, %47, %48, %49, %50, %51, %52, %53, %54, %55, %56, %57, %58, %59, %60, %61, %62, %63}, %64, %65, 1, 1, 1, %66, %67;"
    : "+f"(d[0]), "+f"(d[1]), "+f"(d[2]), "+f"(d[3]), "+f"(d[4]), "+f"(d[5]), "+f"(d[6]), "+f"(d[7]), "+f"(d[8]), "+f"(d[9]), "+f"(d[10]), "+f"(d[11]), "+f"(d[12]), "+f"(d[13]), "+f"(d[14]), "+f"(d[15]), "+f"(d[16]), "+f"(d[17]), "+f"(d[18]), "+f"(d[19]), "+f"(d[20]), "+f"(d[21]), "+f"(d[22]), "+f"(d[23]), "+f"(d[24]), "+f"(d[25]), "+f"(d[26]), "+f"(d[27]), "+f"(d[28]), "+f"(d[29]), "+f"(d[30]), "+f"(d[31]), "+f"(d[32]), "+f"(d[33]), "+f"(d[34]), "+f"(d[35]), "+f"(d[36]), "+f"(d[37]), "+f"(d[38]), "+f"(d[39]), "+f"(d[40]), "+f"(d[41]), "+f"(d[42]), "+f"(d[43]), "+f"(d[44]), "+f"(d[45]), "+f"(d[46]), "+f"(d[47]), "+f"(d[48]), "+f"(d[49]), "+f"(d[50]), "+f"(d[51]), "+f"(d[52]), "+f"(d[53]), "+f"(d[54]), "+f"(d[55]), "+f"(d[56]), "+f"(d[57]), "+f"(d[58]), "+f"(d[59]), "+f"(d[60]), "+f"(d[61]), "+f"(d[62]), "+f"(d[63])
    : "l"(da), "l"(db), "n"(TA), "n"(TB));
}
template<int TA, int TB> __device__ __forceinline__ void wgmma_ss40(float* d, uint64_t da, uint64_t db) {
  asm volatile("wgmma.mma_async.sync.aligned.m64n40k16.f32.bf16.bf16 "
    "{%0, %1, %2, %3, %4, %5, %6, %7, %8, %9, %10, %11, %12, %13, %14, %15, %16, %17, %18, %19}, %20, %21, 1, 1, 1, %22, %23;"
    : "+f"(d[0]), "+f"(d[1]), "+f"(d[2]), "+f"(d[3]), "+f"(d[4]), "+f"(d[5]), "+f"(d[6]), "+f"(d[7]), "+f"(d[8]), "+f"(d[9]), "+f"(d[10]), "+f"(d[11]), "+f"(d[12]), "+f"(d[13]), "+f"(d[14]), "+f"(d[15]), "+f"(d[16]), "+f"(d[17]), "+f"(d[18]), "+f"(d[19])
    : "l"(da), "l"(db), "n"(TA), "n"(TB));
}
template<int TA, int TB> __device__ __forceinline__ void wgmma_ss40_z(float* d, uint64_t da, uint64_t db) {
  asm volatile("wgmma.mma_async.sync.aligned.m64n40k16.f32.bf16.bf16 "
    "{%0, %1, %2, %3, %4, %5, %6, %7, %8, %9, %10, %11, %12, %13, %14, %15, %16, %17, %18, %19}, %20, %21, 0, 1, 1, %22, %23;"
    : "+f"(d[0]), "+f"(d[1]), "+f"(d[2]), "+f"(d[3]), "+f"(d[4]), "+f"(d[5]), "+f"(d[6]), "+f"(d[7]), "+f"(d[8]), "+f"(d[9]), "+f"(d[10]), "+f"(d[11]), "+f"(d[12]), "+f"(d[13]), "+f"(d[14]), "+f"(d[15]), "+f"(d[16]), "+f"(d[17]), "+f"(d[18]), "+f"(d[19])
    : "l"(da), "l"(db), "n"(TA), "n"(TB));
}
template<int TA, int TB> __device__ __forceinline__ void wgmma_ss64(float* d, uint64_t da, uint64_t db) {
  asm volatile("wgmma.mma_async.sync.aligned.m64n64k16.f32.bf16.bf16 "
    "{%0, %1, %2, %3, %4, %5, %6, %7, %8, %9, %10, %11, %12, %13, %14, %15, %16, %17, %18, %19, %20, %21, %22, %23, %24, %25, %26, %27, %28, %29, %30, %31}, %32, %33, 1, 1, 1, %34, %35;"
    : "+f"(d[0]), "+f"(d[1]), "+f"(d[2]), "+f"(d[3]), "+f"(d[4]), "+f"(d[5]), "+f"(d[6]), "+f"(d[7]), "+f"(d[8]), "+f"(d[9]), "+f"(d[10]), "+f"(d[11]), "+f"(d[12]), "+f"(d[13]), "+f"(d[14]), "+f"(d[15]), "+f"(d[16]), "+f"(d[17]), "+f"(d[18]), "+f"(d[19]), "+f"(d[20]), "+f"(d[21]), "+f"(d[22]), "+f"(d[23]), "+f"(d[24]), "+f"(d[25]), "+f"(d[26]), "+f"(d[27]), "+f"(d[28]), "+f"(d[29]), "+f"(d[30]), "+f"(d[31])
    : "l"(da), "l"(db), "n"(TA), "n"(TB));
}
template<int TA, int TB> __device__ __forceinline__ void wgmma_ss64_i(float* d, uint64_t da, uint64_t db) {
  asm volatile("wgmma.mma_async.sync.aligned.m64n64k16.f32.bf16.bf16 "
    "{%0, %1, %2, %3, %4, %5, %6, %7, %8, %9, %10, %11, %12, %13, %14, %15, %16, %17, %18, %19, %20, %21, %22, %23, %24, %25, %26, %27, %28, %29, %30, %31}, %32, %33, 0, 1, 1, %34, %35;"
    : "=f"(d[0]), "=f"(d[1]), "=f"(d[2]), "=f"(d[3]), "=f"(d[4]), "=f"(d[5]), "=f"(d[6]), "=f"(d[7]), "=f"(d[8]), "=f"(d[9]), "=f"(d[10]), "=f"(d[11]), "=f"(d[12]), "=f"(d[13]), "=f"(d[14]), "=f"(d[15]), "=f"(d[16]), "=f"(d[17]), "=f"(d[18]), "=f"(d[19]), "=f"(d[20]), "=f"(d[21]), "=f"(d[22]), "=f"(d[23]), "=f"(d[24]), "=f"(d[25]), "=f"(d[26]), "=f"(d[27]), "=f"(d[28]), "=f"(d[29]), "=f"(d[30]), "=f"(d[31])
    : "l"(da), "l"(db), "n"(TA), "n"(TB));
}
template<int TB> __device__ __forceinline__ void wgmma_rs32(float* d, const uint32_t* a, uint64_t db) {
  asm volatile("wgmma.mma_async.sync.aligned.m64n32k16.f32.bf16.bf16 "
    "{%0, %1, %2, %3, %4, %5, %6, %7, %8, %9, %10, %11, %12, %13, %14, %15}, {%16, %17, %18, %19}, %20, 1, 1, 1, %21;"
    : "+f"(d[0]), "+f"(d[1]), "+f"(d[2]), "+f"(d[3]), "+f"(d[4]), "+f"(d[5]), "+f"(d[6]), "+f"(d[7]), "+f"(d[8]), "+f"(d[9]), "+f"(d[10]), "+f"(d[11]), "+f"(d[12]), "+f"(d[13]), "+f"(d[14]), "+f"(d[15])
    : "r"(a[0]), "r"(a[1]), "r"(a[2]), "r"(a[3]), "l"(db), "n"(TB));
}
template<int TB> __device__ __forceinline__ void wgmma_rs32_i(float* d, const uint32_t* a, uint64_t db) {
  asm volatile("wgmma.mma_async.sync.aligned.m64n32k16.f32.bf16.bf16 "
    "{%0, %1, %2, %3, %4, %5, %6, %7, %8, %9, %10, %11, %12, %13, %14, %15}, {%16, %17, %18, %19}, %20, 0, 1, 1, %21;"
    : "=f"(d[0]), "=f"(d[1]), "=f"(d[2]), "=f"(d[3]), "=f"(d[4]), "=f"(d[5]), "=f"(d[6]), "=f"(d[7]), "=f"(d[8]), "=f"(d[9]), "=f"(d[10]), "=f"(d[11]), "=f"(d[12]), "=f"(d[13]), "=f"(d[14]), "=f"(d[15])
    : "r"(a[0]), "r"(a[1]), "r"(a[2]), "r"(a[3]), "l"(db), "n"(TB));
}
template<int TB> __device__ __forceinline__ void wgmma_rs32_z(float* d, const uint32_t* a, uint64_t db) {
  asm volatile("wgmma.mma_async.sync.aligned.m64n32k16.f32.bf16.bf16 "
    "{%0, %1, %2, %3, %4, %5, %6, %7, %8, %9, %10, %11, %12, %13, %14, %15}, {%16, %17, %18, %19}, %20, 0, 1, 1, %21;"
    : "+f"(d[0]), "+f"(d[1]), "+f"(d[2]), "+f"(d[3]), "+f"(d[4]), "+f"(d[5]), "+f"(d[6]), "+f"(d[7]), "+f"(d[8]), "+f"(d[9]), "+f"(d[10]), "+f"(d[11]), "+f"(d[12]), "+f"(d[13]), "+f"(d[14]), "+f"(d[15])
    : "r"(a[0]), "r"(a[1]), "r"(a[2]), "r"(a[3]), "l"(db), "n"(TB));
}
template<int TB> __device__ __forceinline__ void wgmma_rs8(float* d, const uint32_t* a, uint64_t db) {
  asm volatile("wgmma.mma_async.sync.aligned.m64n8k16.f32.bf16.bf16 "
    "{%0, %1, %2, %3}, {%4, %5, %6, %7}, %8, 1, 1, 1, %9;"
    : "+f"(d[0]), "+f"(d[1]), "+f"(d[2]), "+f"(d[3])
    : "r"(a[0]), "r"(a[1]), "r"(a[2]), "r"(a[3]), "l"(db), "n"(TB));
}
template<int TB> __device__ __forceinline__ void wgmma_rs8_z(float* d, const uint32_t* a, uint64_t db) {
  asm volatile("wgmma.mma_async.sync.aligned.m64n8k16.f32.bf16.bf16 "
    "{%0, %1, %2, %3}, {%4, %5, %6, %7}, %8, 0, 1, 1, %9;"
    : "+f"(d[0]), "+f"(d[1]), "+f"(d[2]), "+f"(d[3])
    : "r"(a[0]), "r"(a[1]), "r"(a[2]), "r"(a[3]), "l"(db), "n"(TB));
}
template<int TB> __device__ __forceinline__ void wgmma_rs256(float* d, const uint32_t* a, uint64_t db) {
  asm volatile("wgmma.mma_async.sync.aligned.m64n256k16.f32.bf16.bf16 "
    "{%0, %1, %2, %3, %4, %5, %6, %7, %8, %9, %10, %11, %12, %13, %14, %15, %16, %17, %18, %19, %20, %21, %22, %23, %24, %25, %26, %27, %28, %29, %30, %31, %32, %33, %34, %35, %36, %37, %38, %39, %40, %41, %42, %43, %44, %45, %46, %47, %48, %49, %50, %51, %52, %53, %54, %55, %56, %57, %58, %59, %60, %61, %62, %63, %64, %65, %66, %67, %68, %69, %70, %71, %72, %73, %74, %75, %76, %77, %78, %79, %80, %81, %82, %83, %84, %85, %86, %87, %88, %89, %90, %91, %92, %93, %94, %95, %96, %97, %98, %99, %100, %101, %102, %103, %104, %105, %106, %107, %108, %109, %110, %111, %112, %113, %114, %115, %116, %117, %118, %119, %120, %121, %122, %123, %124, %125, %126, %127}, {%128, %129, %130, %131}, %132, 1, 1, 1, %133;"
    : "+f"(d[0]), "+f"(d[1]), "+f"(d[2]), "+f"(d[3]), "+f"(d[4]), "+f"(d[5]), "+f"(d[6]), "+f"(d[7]), "+f"(d[8]), "+f"(d[9]), "+f"(d[10]), "+f"(d[11]), "+f"(d[12]), "+f"(d[13]), "+f"(d[14]), "+f"(d[15]), "+f"(d[16]), "+f"(d[17]), "+f"(d[18]), "+f"(d[19]), "+f"(d[20]), "+f"(d[21]), "+f"(d[22]), "+f"(d[23]), "+f"(d[24]), "+f"(d[25]), "+f"(d[26]), "+f"(d[27]), "+f"(d[28]), "+f"(d[29]), "+f"(d[30]), "+f"(d[31]), "+f"(d[32]), "+f"(d[33]), "+f"(d[34]), "+f"(d[35]), "+f"(d[36]), "+f"(d[37]), "+f"(d[38]), "+f"(d[39]), "+f"(d[40]), "+f"(d[41]), "+f"(d[42]), "+f"(d[43]), "+f"(d[44]), "+f"(d[45]), "+f"(d[46]), "+f"(d[47]), "+f"(d[48]), "+f"(d[49]), "+f"(d[50]), "+f"(d[51]), "+f"(d[52]), "+f"(d[53]), "+f"(d[54]), "+f"(d[55]), "+f"(d[56]), "+f"(d[57]), "+f"(d[58]), "+f"(d[59]), "+f"(d[60]), "+f"(d[61]), "+f"(d[62]), "+f"(d[63]), "+f"(d[64]), "+f"(d[65]), "+f"(d[66]), "+f"(d[67]), "+f"(d[68]), "+f"(d[69]), "+f"(d[70]), "+f"(d[71]), "+f"(d[72]), "+f"(d[73]), "+f"(d[74]), "+f"(d[75]), "+f"(d[76]), "+f"(d[77]), "+f"(d[78]), "+f"(d[79]), "+f"(d[80]), "+f"(d[81]), "+f"(d[82]), "+f"(d[83]), "+f"(d[84]), "+f"(d[85]), "+f"(d[86]), "+f"(d[87]), "+f"(d[88]), "+f"(d[89]), "+f"(d[90]), "+f"(d[91]), "+f"(d[92]), "+f"(d[93]), "+f"(d[94]), "+f"(d[95]), "+f"(d[96]), "+f"(d[97]), "+f"(d[98]), "+f"(d[99]), "+f"(d[100]), "+f"(d[101]), "+f"(d[102]), "+f"(d[103]), "+f"(d[104]), "+f"(d[105]), "+f"(d[106]), "+f"(d[107]), "+f"(d[108]), "+f"(d[109]), "+f"(d[110]), "+f"(d[111]), "+f"(d[112]), "+f"(d[113]), "+f"(d[114]), "+f"(d[115]), "+f"(d[116]), "+f"(d[117]), "+f"(d[118]), "+f"(d[119]), "+f"(d[120]), "+f"(d[121]), "+f"(d[122]), "+f"(d[123]), "+f"(d[124]), "+f"(d[125]), "+f"(d[126]), "+f"(d[127])
    : "r"(a[0]), "r"(a[1]), "r"(a[2]), "r"(a[3]), "l"(db), "n"(TB));
}

constexpr int S_ = 2048, D_ = 1024, F_ = 3584;

__device__ __align__(1024) bf16 g_xn[S_ * D_];
__device__ __align__(1024) bf16 g_h[S_ * F_];
__device__ __align__(1024) bf16 g_o[S_ * D_];
__device__ __align__(1024) bf16 g_px[S_ * D_];
constexpr int ACC_HEAD = 2048 + 64;
constexpr int NCOPY = 2;
__device__ __align__(1024) float g_acc[NCOPY * 8 * 4 * ACC_HEAD];
__device__ __align__(1024) uint8_t g_kvt[8 * 17408];
__device__ __align__(1024) float2 g_stats[S_];
__device__ __align__(1024) float g_csp[8 * 8 * 256];
__device__ __align__(1024) unsigned g_flags[256 * 32];

constexpr int FL_XN = 0, FL_KV2 = 16, FL_KV = 24, FL_H = 32, FL_O = 80, FL_DONE = 96, FL_ZERO = 97, FL_PX = 105, FL_CS = 233, FL_N = 241;

constexpr uint32_t SLOT1 = 49152, SLOT2 = 32768;
constexpr uint32_t OFF_WPHI = 196608;
constexpr uint32_t OFF_TP = OFF_WPHI + 8192;
constexpr uint32_t OFF_TV = OFF_TP + 16384;
constexpr uint32_t OFF_Z = OFF_TV + 8192;
constexpr uint32_t OFF_BAR = OFF_Z + 1024;
constexpr uint32_t OFF_B1 = OFF_BAR + 368;
constexpr uint32_t OFF_B2 = OFF_B1 + 896;
constexpr uint32_t OFF_CST = OFF_B2 + 256;
constexpr uint32_t OFF_ZST = OFF_CST + 16;
constexpr uint32_t SMEM_BYTES = OFF_ZST + 512;
constexpr uint32_t B_FULL1 = 0, B_EMPTY1 = 4, B_FULL2 = 8, B_EMPTY2 = 14, B_EV = 20, B_MISC = 25, B_RDY = 26, B_KVT = 30, B_KVP = 31, B_EVK = 32, B_XT = 33, B_EV5 = 34, B_EV6 = 35, B_PXT = 36, B_EVLN = 37, B_EVCS = 38, B_RXN = 39, B_TAB = 40;

__device__ __forceinline__ uint32_t smem_u32(const void* p) { return (uint32_t)__cvta_generic_to_shared(p); }
__device__ __forceinline__ void mbar_init(uint32_t bar, uint32_t cnt) { asm volatile("mbarrier.init.shared::cta.b64 [%0], %1;" ::"r"(bar), "r"(cnt) : "memory"); }
__device__ __forceinline__ void mbar_expect_tx(uint32_t bar, uint32_t bytes) { asm volatile("mbarrier.arrive.expect_tx.shared::cta.b64 _, [%0], %1;" ::"r"(bar), "r"(bytes) : "memory"); }
__device__ __forceinline__ void mbar_arrive(uint32_t bar) { asm volatile("mbarrier.arrive.shared::cta.b64 _, [%0];" ::"r"(bar) : "memory"); }
__device__ __forceinline__ void mbar_wait(uint32_t bar, uint32_t parity) {
  asm volatile("{\n.reg .pred p;\n.reg .u32 n;\n"
               "mbarrier.try_wait.parity.shared::cta.b64 p, [%0], %1;\n@p bra DONE;\nmov.u32 n, 0;\n"
               "LOOP:\nmbarrier.try_wait.parity.shared::cta.b64 p, [%0], %1;\n@p bra DONE;\n"
               "add.u32 n, n, 1;\nsetp.gt.u32 p, n, 4194304;\n@p trap;\nbra LOOP;\nDONE:\n}" ::"r"(bar), "r"(parity) : "memory");
}
__device__ __forceinline__ void flag_wait(const unsigned* ptr, unsigned target) {
  asm volatile("{\n.reg .pred p;\n.reg .u32 n, v;\nmov.u32 n, 0;\n"
               "LOOP:\nld.acquire.gpu.global.u32 v, [%0];\nsetp.ge.u32 p, v, %1;\n@p bra DONE;\n"
               "add.u32 n, n, 1;\nsetp.gt.u32 p, n, 2097152;\n@p trap;\nbra LOOP;\nDONE:\n}" ::"l"(ptr), "r"(target) : "memory");
}
__device__ __forceinline__ void flag_add(unsigned* p) { asm volatile("red.relaxed.gpu.global.add.u32 [%0], 1;" ::"l"(p) : "memory"); }
__device__ __forceinline__ void fence_gpu() { asm volatile("fence.acq_rel.gpu;" ::: "memory"); }
__device__ __forceinline__ void fence_proxy_async_smem() { asm volatile("fence.proxy.async.shared::cta;" ::: "memory"); }
__device__ __forceinline__ void bar_sync(int id, int n) { asm volatile("bar.sync %0, %1;" ::"r"(id), "r"(n) : "memory"); }
__device__ __forceinline__ void tma_load_2d(uint32_t dst, const CUtensorMap* m, uint32_t bar, int c0, int c1) {
  asm volatile("cp.async.bulk.tensor.2d.shared::cluster.global.mbarrier::complete_tx::bytes [%0], [%1, {%3, %4}], [%2];" ::"r"(dst), "l"(m), "r"(bar), "r"(c0), "r"(c1) : "memory");
}
__device__ __forceinline__ void tma_load_3d_mc(uint32_t dst, const CUtensorMap* m, uint32_t bar, int c0, int c1, int c2) {
  asm volatile("cp.async.bulk.tensor.3d.shared::cluster.global.mbarrier::complete_tx::bytes.multicast::cluster [%0], [%1, {%3, %4, %5}], [%2], %6;" ::"r"(dst), "l"(m), "r"(bar), "r"(c0), "r"(c1), "r"(c2), "h"((uint16_t)3) : "memory");
}
__device__ __forceinline__ void tma_prefetch_3d(const CUtensorMap* m, int c0, int c1, int c2) {
  asm volatile("cp.async.bulk.prefetch.tensor.3d.L2.global.tile [%0, {%1, %2, %3}];" ::"l"(m), "r"(c0), "r"(c1), "r"(c2) : "memory");
}
__device__ __forceinline__ void tma_store_2d(const CUtensorMap* m, uint32_t src, int c0, int c1) {
  asm volatile("cp.async.bulk.tensor.2d.global.shared::cta.bulk_group [%0, {%2, %3}], [%1];" ::"l"(m), "r"(src), "r"(c0), "r"(c1) : "memory");
}
__device__ __forceinline__ void bulk_commit() { asm volatile("cp.async.bulk.commit_group;" ::: "memory"); }
__device__ __forceinline__ void bulk_wait_read() { asm volatile("cp.async.bulk.wait_group.read 0;" ::: "memory"); }
__device__ __forceinline__ void bulk_wait_all() { asm volatile("cp.async.bulk.wait_group 0;" ::: "memory"); }
__device__ __forceinline__ void wgmma_fence() { asm volatile("wgmma.fence.sync.aligned;" ::: "memory"); }
__device__ __forceinline__ void wgmma_commit() { asm volatile("wgmma.commit_group.sync.aligned;" ::: "memory"); }
template <int N> __device__ __forceinline__ void wgmma_wait() { asm volatile("wgmma.wait_group.sync.aligned %0;" ::"n"(N) : "memory"); }
template <int N> __device__ __forceinline__ void fence_regs(float* d) {
#pragma unroll
  for (int i = 0; i < N; i++) asm volatile("" : "+f"(d[i])::"memory");
}
__device__ __forceinline__ void stsm4(uint32_t addr, uint32_t a, uint32_t b, uint32_t c, uint32_t d) {
  asm volatile("stmatrix.sync.aligned.m8n8.x4.shared.b16 [%0], {%1, %2, %3, %4};" ::"r"(addr), "r"(a), "r"(b), "r"(c), "r"(d) : "memory");
}
template <int X> __device__ __forceinline__ void stsm4x(uint32_t addr, uint32_t a, uint32_t b, uint32_t c, uint32_t d) {
  asm volatile("{\n.reg .b32 t;\nxor.b32 t, %0, %5;\nstmatrix.sync.aligned.m8n8.x4.shared.b16 [t], {%1, %2, %3, %4};\n}" ::"r"(addr), "r"(a), "r"(b), "r"(c), "r"(d), "n"(X) : "memory");
}
__device__ __forceinline__ uint32_t pack_bf16(float lo, float hi) {
  uint32_t r; asm("cvt.rn.bf16x2.f32 %0, %1, %2;" : "=r"(r) : "f"(hi), "f"(lo)); return r;
}
__device__ __forceinline__ float lo_f(uint32_t u) { return __uint_as_float(u << 16); }
__device__ __forceinline__ float hi_f(uint32_t u) { return __uint_as_float(u & 0xffff0000u); }
__device__ __forceinline__ float bf16r(float x) { return __uint_as_float(pack_bf16(x, 0.f) << 16); }
__device__ __forceinline__ uint32_t add_bf16x2(uint32_t a, uint32_t b) { uint32_t r; asm("add.rn.bf16x2 %0, %1, %2;" : "=r"(r) : "r"(a), "r"(b)); return r; }
__device__ __forceinline__ uint32_t mul_bf16x2(uint32_t a, uint32_t b) { uint32_t r; asm("mul.rn.bf16x2 %0, %1, %2;" : "=r"(r) : "r"(a), "r"(b)); return r; }
__device__ __forceinline__ uint32_t max_bf16x2(uint32_t a, uint32_t b) { uint32_t r; asm("max.bf16x2 %0, %1, %2;" : "=r"(r) : "r"(a), "r"(b)); return r; }
__device__ __forceinline__ uint32_t min_bf16x2(uint32_t a, uint32_t b) { uint32_t r; asm("min.bf16x2 %0, %1, %2;" : "=r"(r) : "r"(a), "r"(b)); return r; }
__device__ __forceinline__ float ex2f(float x) { float r; asm("ex2.approx.ftz.f32 %0, %1;" : "=f"(r) : "f"(x)); return r; }
__device__ __forceinline__ float rcpf(float x) { float r; asm("rcp.approx.ftz.f32 %0, %1;" : "=f"(r) : "f"(x)); return r; }
__device__ __forceinline__ float tanhf_a(float x) { float r; asm("tanh.approx.f32 %0, %1;" : "=f"(r) : "f"(x)); return r; }
__device__ __forceinline__ uint32_t lds32(uint32_t a) { uint32_t r; asm volatile("ld.shared.u32 %0, [%1];" : "=r"(r) : "r"(a)); return r; }
__device__ __forceinline__ void sts128(uint32_t a, uint4 v) { asm volatile("st.shared.v4.u32 [%0], {%1, %2, %3, %4};" ::"r"(a), "r"(v.x), "r"(v.y), "r"(v.z), "r"(v.w) : "memory"); }
__device__ __forceinline__ uint4 ldg128_nc(const void* p) { uint4 v; asm volatile("ld.global.nc.v4.u32 {%0, %1, %2, %3}, [%4];" : "=r"(v.x), "=r"(v.y), "=r"(v.z), "=r"(v.w) : "l"(p)); return v; }
__device__ __forceinline__ float4 ldg128_cg(const float* p) { float4 v; asm volatile("ld.global.cg.v4.f32 {%0, %1, %2, %3}, [%4];" : "=f"(v.x), "=f"(v.y), "=f"(v.z), "=f"(v.w) : "l"(p) : "memory"); return v; }
template <int R> __device__ __forceinline__ void reg_alloc() { asm volatile("setmaxnreg.inc.sync.aligned.u32 %0;" ::"n"(R)); }
template <int R> __device__ __forceinline__ void reg_dealloc() { asm volatile("setmaxnreg.dec.sync.aligned.u32 %0;" ::"n"(R)); }

constexpr uint32_t HI128 = (1024u >> 4) | (1u << 30);
constexpr uint32_t HI64 = (512u >> 4) | (2u << 30);
constexpr uint32_t LBO_1 = 1u << 16;
constexpr uint32_t LBO_B = (4096u >> 4) << 16;
__device__ __forceinline__ uint64_t dsc(uint32_t lo, uint32_t hi) { return ((uint64_t)hi << 32) | lo; }

__device__ __forceinline__ void arrive_if(uint32_t addr, uint32_t tid, uint32_t thr) {
  asm volatile("{\n.reg .pred p;\nsetp.lt.u32 p, %1, %2;\n@p mbarrier.arrive.shared::cluster.b64 _, [%0];\n}" ::"r"(addr), "r"(tid), "r"(thr) : "memory");
}

template <int N> __device__ __forceinline__ void issue_main(float* acc, uint32_t alo, uint32_t blo, int sd0) {
  constexpr uint32_t HALF = (N / 64) * 4096;
#pragma unroll
  for (int kk = 0; kk < 4; kk++) {
    const uint64_t da = dsc(alo + kk * 2, HI128);
    const uint64_t db = dsc(blo + (((kk >> 1) * HALF + (kk & 1) * 2048) >> 4), HI128);
    if (kk == 0) {
      if constexpr (N == 256) wgmma_ss256_p<0, 1>(acc, da, db, sd0);
      else if constexpr (N == 192) wgmma_ss192_p<0, 1>(acc, da, db, sd0);
      else wgmma_ss128_p<0, 1>(acc, da, db, sd0);
    } else {
      if constexpr (N == 256) wgmma_ss256<0, 1>(acc, da, db);
      else if constexpr (N == 192) wgmma_ss192<0, 1>(acc, da, db);
      else wgmma_ss128<0, 1>(acc, da, db);
    }
  }
}

__device__ __forceinline__ void bulk_store(void* g, uint32_t s, uint32_t bytes) {
  asm volatile("cp.async.bulk.global.shared::cta.bulk_group [%0], [%1], %2;" ::"l"(g), "r"(s), "r"(bytes) : "memory");
}
__device__ __forceinline__ void bar_arrive(int id, int n) { asm volatile("bar.arrive %0, %1;" ::"r"(id), "r"(n) : "memory"); }
__device__ __forceinline__ void tma_prefetch_2d(const CUtensorMap* m, int c0, int c1) {
  asm volatile("cp.async.bulk.prefetch.tensor.2d.L2.global.tile [%0, {%1, %2}];" ::"l"(m), "r"(c0), "r"(c1) : "memory");
}
__device__ __forceinline__ void done_and_reset() {
  unsigned old;
  asm volatile("atom.relaxed.gpu.global.add.u32 %0, [%1], 1;" : "=r"(old) : "l"(&g_flags[FL_DONE * 32]) : "memory");
  if (old == 255) { for (int i = 0; i < FL_N; i++) g_flags[i * 32] = 0; }
}
__device__ __forceinline__ bool elect_one() {
  uint32_t p;
  asm volatile("{\n.reg .pred P;\nelect.sync _|P, 0xffffffff;\nselp.u32 %0, 1, 0, P;\n}" : "=r"(p));
  return p != 0;
}
__device__ __forceinline__ void mbar_probe(uint32_t bar, uint32_t parity) {
  asm volatile("mbarrier.test_wait.parity.shared::cta.b64 pok, [%0], %1;" ::"r"(bar), "r"(parity) : "memory");
}
__device__ __forceinline__ void mbar_probe_clear() { asm volatile("setp.ne.u32 pok, 0, 0;" ::: "memory"); }
__device__ __forceinline__ void mbar_wait_probed(uint32_t bar, uint32_t parity) {
  asm volatile("{\n.reg .pred p;\n.reg .u32 n;\n@pok bra DONE;\nmov.u32 n, 0;\n"
               "LOOP:\nmbarrier.try_wait.parity.shared::cta.b64 p, [%0], %1;\n@p bra DONE;\n"
               "add.u32 n, n, 1;\nsetp.gt.u32 p, n, 4194304;\n@p trap;\nbra LOOP;\nDONE:\n}" ::"r"(bar), "r"(parity) : "memory");
}
template <int N> __device__ __forceinline__ void pin(uint32_t* r) {
#pragma unroll
  for (int i = 0; i < N; i++) asm volatile("" : "+r"(r[i]));
}
template <int N> __device__ __forceinline__ void pinf(float* r) {
#pragma unroll
  for (int i = 0; i < N; i++) asm volatile("" : "+f"(r[i]));
}
__device__ __forceinline__ float gelu_half(float h) {
  const float u = h * fmaf(h * h, 8.0f * 0.7978845608028654f * 0.044715f, 2.0f * 0.7978845608028654f);
  return fmaf(h, tanhf_a(u), h);
}
constexpr float L2E = 1.4426950408889634f;
__device__ __forceinline__ uint32_t anchor(uint32_t zero) {
  uint32_t c; asm volatile("mov.u32 %0, %%clock;" : "=r"(c)); return c & zero;
}
__device__ __forceinline__ float lo_fa(uint32_t u, uint32_t z) { return __uint_as_float(__byte_perm(u, 0u, 0x1044u ^ z)); }
__device__ __forceinline__ float hi_fa(uint32_t u, uint32_t z) { return __uint_as_float(u & (0xffff0000u ^ z)); }
__device__ __forceinline__ uint32_t quad_max2(uint32_t c) {
  const uint32_t a = __shfl_xor_sync(0xffffffffu, c, 1), b = __shfl_xor_sync(0xffffffffu, c, 2), d = __shfl_xor_sync(0xffffffffu, c, 3);
  return max_bf16x2(max_bf16x2(c, a), max_bf16x2(b, d));
}
__device__ __forceinline__ float quad_sum(float c) {
  const float a = __shfl_xor_sync(0xffffffffu, c, 1), b = __shfl_xor_sync(0xffffffffu, c, 2), d = __shfl_xor_sync(0xffffffffu, c, 3);
  return (c + a) + (b + d);
}
template <bool SCALE> __device__ __forceinline__ void hh_part1(const float* p, uint32_t* u, float* M, float rA = 1.f, float rB = 1.f) {
#pragma unroll
  for (int i = 0; i < 8; i++) {
    if (SCALE) { const float r = (i & 1) ? rB : rA; u[i] = pack_bf16(p[2 * i] * r, p[2 * i + 1] * r); }
    else u[i] = pack_bf16(p[2 * i], p[2 * i + 1]);
  }
  uint32_t c[2];
#pragma unroll
  for (int h = 0; h < 2; h++) {
    const uint32_t mx = max_bf16x2(max_bf16x2(u[h], u[2 + h]), max_bf16x2(u[4 + h], u[6 + h]));
    const uint32_t mn = min_bf16x2(min_bf16x2(u[h], u[2 + h]), min_bf16x2(u[4 + h], u[6 + h])) ^ 0x80008000u;
    c[h] = max_bf16x2(__byte_perm(mx, mn, 0x5410), __byte_perm(mx, mn, 0x7632));
  }
#pragma unroll
  for (int h = 0; h < 2; h++) {
    c[h] = quad_max2(c[h]);
    M[2 * h] = -L2E * lo_f(c[h]);
    M[2 * h + 1] = -L2E * hi_f(c[h]);
  }
  pin<8>(u); pinf<4>(M);
}
template <int H> __device__ __forceinline__ void hh_part2a(const uint32_t* u, const float* M, float* e, float* s, uint32_t z) {
  float sp[4], sn[4];
#pragma unroll
  for (int b = 0; b < 4; b++) {
    const float x0 = lo_fa(u[2 * b + H], z), x1 = hi_fa(u[2 * b + H], z);
    e[2 * b] = ex2f(fmaf(x0, L2E, M[2 * H])); e[2 * b + 1] = ex2f(fmaf(x1, L2E, M[2 * H]));
    e[8 + 2 * b] = ex2f(fmaf(x0, -L2E, M[2 * H + 1])); e[8 + 2 * b + 1] = ex2f(fmaf(x1, -L2E, M[2 * H + 1]));
    sp[b] = e[2 * b] + e[2 * b + 1];
    sn[b] = e[8 + 2 * b] + e[8 + 2 * b + 1];
  }
  s[0] = (sp[0] + sp[1]) + (sp[2] + sp[3]); s[1] = (sn[0] + sn[1]) + (sn[2] + sn[3]);
  pinf<16>(e); pinf<2>(s);
}
__device__ __forceinline__ void hh_sums(float* s, uint32_t z) {
  s[0] = rcpf(quad_sum(s[0] + __uint_as_float(z)));
  s[1] = rcpf(quad_sum(s[1] + __uint_as_float(z)));
}
template <int H, bool SPLIT> __device__ __forceinline__ void hh_scale(const float* e, const float* s, uint32_t* phi) {
#pragma unroll
  for (int b = 0; b < 4; b++) {
    const int ip = SPLIT ? b : 2 * b + H, in = SPLIT ? 4 + b : 8 + 2 * b + H;
    phi[ip] = pack_bf16(e[2 * b] * s[0], e[2 * b + 1] * s[0]);
    phi[in] = pack_bf16(e[8 + 2 * b] * s[1], e[8 + 2 * b + 1] * s[1]);
    asm volatile("" : "+r"(phi[ip]), "+r"(phi[in]));
  }
}
template <bool TIED> __device__ __forceinline__ void issue_phi(float* p, const uint32_t* a, uint32_t wlo) {
  if (TIED) wgmma_rs32_z<1>(p, a, dsc(wlo, HI128)); else wgmma_rs32_i<1>(p, a, dsc(wlo, HI128));
  wgmma_rs32<1>(p, a + 4, dsc(wlo + (2048 >> 4), HI128));
}
__device__ __forceinline__ uint32_t wphi_lo(uint32_t sd, int hh) { return ((sd + OFF_WPHI + (hh >> 1) * 4096 + (hh & 1) * 64) >> 4) | LBO_1; }

__device__ __forceinline__ void lds64(uint32_t* r, uint32_t a) { asm volatile("ld.shared.v2.u32 {%0, %1}, [%2];" : "=r"(r[0]), "=r"(r[1]) : "r"(a)); }
template <int I0> __device__ __forceinline__ void gelu4(uint32_t* st, const uint32_t* hb, uint32_t z) {
#pragma unroll
  for (int i = I0; i < I0 + 4; i++) {
    uint32_t h2;
    asm("fma.rn.bf16x2 %0, %1, %2, %3;" : "=r"(h2) : "r"(st[i]), "r"(0x3f003f00u ^ z), "r"((i & 2) ? hb[1] : hb[0]));
    st[i] = pack_bf16(gelu_half(lo_f(h2)), gelu_half(hi_f(h2)));
  }
  pin<4>(st + I0);
}

__global__ void __cluster_dims__(2, 1, 1) __launch_bounds__(384, 1)
fused_kernel(const __grid_constant__ CUtensorMap tm_xn, const __grid_constant__ CUtensorMap tm_h, const __grid_constant__ CUtensorMap tm_o,
             const __grid_constant__ CUtensorMap tm_wqkv, const __grid_constant__ CUtensorMap tm_w1a, const __grid_constant__ CUtensorMap tm_w1b,
             const __grid_constant__ CUtensorMap tm_w2, const __grid_constant__ CUtensorMap tm_wo,
             const __grid_constant__ CUtensorMap tm_hst, const __grid_constant__ CUtensorMap tm_x, const __grid_constant__ CUtensorMap tm_ost, const __grid_constant__ CUtensorMap tm_out,
             const __grid_constant__ CUtensorMap tm_px,
             const bf16* __restrict__ x, const bf16* __restrict__ wphi, const bf16* __restrict__ b1, const bf16* __restrict__ b2) {
  asm volatile(".reg .pred pok;");
  extern __shared__ __align__(1024) uint8_t smem_raw[];
  const uint32_t sb = smem_u32(smem_raw);
  const uint32_t sd = sb & 0x3FFFFu;
  const uint32_t bars = sb + OFF_BAR;
  const int warp = __shfl_sync(0xffffffffu, threadIdx.x >> 5, 0), lane = threadIdx.x & 31;
  uint32_t rank; asm volatile("mov.u32 %0, %%cluster_ctarank;" : "=r"(rank));
  const int cl = blockIdx.x >> 1;
  const int m = 2 * (cl & 7) + (int)rank, j = cl >> 3;

  if (threadIdx.x == 0) {
    if (sb & 1023) asm volatile("trap;");
    for (int s = 0; s < 4; s++) { mbar_init(bars + (B_FULL1 + s) * 8, 1); mbar_init(bars + (B_EMPTY1 + s) * 8, 4); }
    for (int s = 0; s < 6; s++) { mbar_init(bars + (B_FULL2 + s) * 8, 1); mbar_init(bars + (B_EMPTY2 + s) * 8, 4); }
    for (int s = 0; s < 5; s++) mbar_init(bars + (B_EV + s) * 8, 8);
    mbar_init(bars + B_MISC * 8, 64);
    for (int s = 0; s < 4; s++) mbar_init(bars + (B_RDY + s) * 8, 1);
    mbar_init(bars + B_KVT * 8, 1);
    mbar_init(bars + B_KVP * 8, 1);
    mbar_init(bars + B_EVK * 8, 8);
    mbar_init(bars + B_XT * 8, 1);
    mbar_init(bars + B_EV5 * 8, 8);
    mbar_init(bars + B_EV6 * 8, 8);
    mbar_init(bars + B_PXT * 8, 1);
    mbar_init(bars + B_EVLN * 8, 8);
    mbar_init(bars + B_EVCS * 8, 2);
    mbar_init(bars + B_RXN * 8, 1);
    mbar_init(bars + B_TAB * 8, 65);
    asm volatile("fence.mbarrier_init.release.cluster;" ::: "memory");
  }
  if (warp == 1 && elect_one()) {
    const int k = m & ~1 & 15;
    tma_prefetch_3d(&tm_wqkv, 0, k * 64 + rank * 32, 16 + 2 * j);
    tma_prefetch_3d(&tm_wqkv, 0, k * 64 + rank * 32, 32 + 2 * j);
    tma_prefetch_2d(&tm_x, k * 64, m * 128);
  }
  if (warp == 2 || warp == 3) {
    const int t = threadIdx.x - 64;
    sts128(sb + OFF_Z + t * 16, make_uint4(0x3f803f80u, 0x3f803f80u, 0x3f803f80u, 0x3f803f80u));
    if (t == 0) sts128(sb + OFF_CST, make_uint4(0u, 0u, 0u, 0u));
    for (int q = t; q < 132; q += 64) sts128(sb + OFF_TV + 1024 + q * 16, make_uint4(0u, 0u, 0u, 0u));
    fence_proxy_async_smem();
  }
  __syncthreads();
  asm volatile("barrier.cluster.arrive.relaxed.aligned;\nbarrier.cluster.wait.aligned;" ::: "memory");

  if (warp < 4) {
    reg_dealloc<40>();
    if (warp == 0) {
      if (elect_one()) {
        const int kh = rank * 32, arow = m * 128;
#pragma unroll 1
        for (int s = 0; s < 16; s++) {
          const int slot = s & 3, k = ((m & ~1) + s) & 15;
          const uint32_t fb = bars + (B_FULL1 + slot) * 8, sa = sb + slot * SLOT1, d = sa + 16384 + rank * 16384;
          const int kr = k * 64 + kh;
          if (s >= 4) mbar_wait(bars + (B_EMPTY1 + slot) * 8, ((s >> 2) & 1) ^ 1);
          mbar_expect_tx(fb, 16384 + 32768);
          tma_load_3d_mc(d, &tm_wqkv, fb, 0, kr, 16 + 2 * j);
          tma_load_3d_mc(d + 8192, &tm_wqkv, fb, 0, kr, 32 + 2 * j);
          tma_load_2d(sa, &tm_x, fb, k * 64, arow);
        }
#pragma unroll 1
        for (int g = 16; g < 48; g++) {
          const int k = g & 15, slot = g & 3;
          const uint32_t fb = bars + (B_FULL1 + slot) * 8, sa = sb + slot * SLOT1, d = sa + 16384 + rank * 12288;
          const int kr = k * 64 + kh, ch = 7 * j + (g >= 32 ? 3 : 0);
          mbar_wait(bars + (B_EMPTY1 + slot) * 8, ((g >> 2) & 1) ^ 1);
          mbar_expect_tx(fb, 16384 + 24576);
          tma_load_3d_mc(d, &tm_w1a, fb, 0, kr, ch);
          if (g == 16) mbar_wait(bars + B_RXN * 8, 0);
          tma_load_2d(sa, &tm_xn, fb, k * 64, arow);
        }
#pragma unroll 1
        for (int k = 0; k < 16; k++) {
          const int slot = k & 3;
          const uint32_t fb = bars + (B_FULL1 + slot) * 8, sa = sb + slot * SLOT1, d = sa + 16384 + rank * 12288;
          const int kr = k * 64 + kh;
          mbar_wait(bars + (B_EMPTY1 + slot) * 8, ((k >> 2) & 1) ^ 1);
          mbar_expect_tx(fb, 16384 + 24576);
          tma_load_3d_mc(d, &tm_w1b, fb, 0, kr, 7 * j + 6);
          tma_load_3d_mc(d + 4096, &tm_wqkv, fb, 0, kr, 2 * j);
          tma_load_2d(sa, &tm_xn, fb, k * 64, arow);
        }
        {
          const int jb = 4 * (j & 1);
          int kc = 448 * jb, c3 = 0;
#pragma unroll 1
          for (int g = 0; g < 24; g++) {
            const int slot = g & 3;
            const uint32_t fb = bars + (B_FULL1 + slot) * 8, sa = sb + slot * SLOT1, d = sa + 16384 + rank * 16384;
            const int rdy = g == 0 ? 0 : g == 12 ? 1 : -1;
            mbar_wait(bars + (B_EMPTY1 + slot) * 8, ((g >> 2) & 1) ^ 1);
            mbar_expect_tx(fb, 16384 + 32768);
            tma_load_3d_mc(d, &tm_w2, fb, 0, kc + kh, 2 * j);
            tma_load_3d_mc(d + 8192, &tm_w2, fb, 0, kc + kh, 2 * (j ^ 1));
            if (rdy >= 0) mbar_wait(bars + (B_RDY + rdy) * 8, 0);
            tma_load_2d(sa, &tm_h, fb, kc, arow);
            if (g == 11) { kc = 448 * jb + 192; c3 = 0; }
            else if (++c3 == 3) { c3 = 0; kc += 320; }
            else kc += 64;
          }
        }
        int slot = 0; uint32_t ph = 1;
#pragma unroll 1
        for (int g = 0; g < 24; g++) {
          const uint32_t fb = bars + (B_FULL2 + slot) * 8, sA = sb + slot * SLOT2, d = sA + 16384 + rank * 8192;
          const int kc = g < 8 ? 448 * g + 384 : (g - 8) * 64;
          if (g < 6) {
            mbar_wait(bars + (B_EMPTY1 + (g * 2) / 3) * 8, 1);
            mbar_wait(bars + (B_EMPTY1 + (g * 2 + 1) / 3) * 8, 1);
          } else {
            mbar_wait(bars + (B_EMPTY2 + slot) * 8, ph);
          }
          mbar_expect_tx(fb, 32768);
          tma_load_3d_mc(d, g < 8 ? &tm_w2 : &tm_wo, fb, 0, kc + kh, 2 * j);
          if (g == 0) mbar_wait(bars + (B_RDY + 2) * 8, 0);
          if (g == 8) mbar_wait(bars + (B_RDY + 3) * 8, 0);
          tma_load_2d(sA, g < 8 ? &tm_h : &tm_o, fb, kc, arow);
          if (++slot == 6) { slot = 0; ph ^= 1; }
        }
#pragma unroll 1
        for (int i = 0; i < 6; i++) {
          mbar_wait(bars + (B_EMPTY2 + slot) * 8, ph);
          if (++slot == 6) { slot = 0; ph ^= 1; }
        }
      }
    } else if (warp == 1) {
      if (elect_one()) {
        unsigned* fh = &g_flags[(FL_H + m * 3) * 32];
        for (int c = 0; c < NCOPY; c++) bulk_store(g_acc + (c * 8 + j) * 4 * ACC_HEAD + m * 528, sb + OFF_TV + 1024, 2112);
        bulk_commit(); bulk_wait_all();
        fence_gpu(); flag_add(&g_flags[(FL_ZERO + j) * 32]);
        mbar_wait(bars + B_EVLN * 8, 0); fence_gpu(); flag_add(&g_flags[(FL_XN + m) * 32]);
        flag_wait(&g_flags[(FL_XN + m) * 32], 8); mbar_arrive(bars + B_RXN * 8);
        mbar_expect_tx(bars + B_TAB * 8, 2048);
        for (int c = 0; c < 2; c++)
          asm volatile("cp.async.bulk.shared::cluster.global.mbarrier::complete_tx::bytes [%0], [%1], %2, [%3];"
                       ::"r"(sb + OFF_TV + c * 4096), "l"(g_stats + m * 128), "r"(1024), "r"(bars + B_TAB * 8) : "memory");
        flag_wait(&g_flags[(FL_ZERO + j) * 32], 16); mbar_arrive(bars + B_KVP * 8);
        mbar_wait(bars + (B_EV + 0) * 8, 0); fence_gpu(); flag_add(&g_flags[(FL_KV + j) * 32]);
        mbar_wait(bars + (B_EV + 1) * 8, 0); fence_gpu(); flag_add(fh);
        flag_wait(fh, 8); mbar_arrive(bars + (B_RDY + 0) * 8);
        mbar_wait(bars + (B_EV + 2) * 8, 0); fence_gpu(); flag_add(fh + 32);
        flag_wait(&g_flags[(FL_KV2 + j) * 32], 16);
        mbar_wait(bars + B_EVK * 8, 0);
        mbar_expect_tx(bars + B_KVT * 8, 16384 + 512);
        asm volatile("cp.async.bulk.shared::cluster.global.mbarrier::complete_tx::bytes [%0], [%1], %2, [%3];"
                     ::"r"(sb + OFF_TP), "l"(g_kvt + j * 17408), "r"(16384), "r"(bars + B_KVT * 8) : "memory");
        asm volatile("cp.async.bulk.shared::cluster.global.mbarrier::complete_tx::bytes [%0], [%1], %2, [%3];"
                     ::"r"(sb + OFF_Z), "l"(g_kvt + j * 17408 + 16384), "r"(512), "r"(bars + B_KVT * 8) : "memory");
        flag_wait(fh + 32, 8); mbar_arrive(bars + (B_RDY + 1) * 8);
        mbar_wait(bars + (B_EV + 3) * 8, 0); fence_gpu(); flag_add(fh + 64);
        flag_wait(fh + 64, 8); mbar_arrive(bars + (B_RDY + 2) * 8);
        mbar_wait(bars + (B_EV + 4) * 8, 0); fence_gpu(); flag_add(&g_flags[(FL_O + m) * 32]);
        flag_wait(&g_flags[(FL_O + m) * 32], 8); mbar_arrive(bars + (B_RDY + 3) * 8);
        done_and_reset();
      }
    } else {
      const int t = threadIdx.x - 64;
#pragma unroll 2
      for (int q = t; q < 512; q += 64) {
        const int hh = q >> 7, d = (q >> 2) & 31, cf = q & 3;
        const uint4 v = ldg128_nc(wphi + (size_t)(4 * j + hh) * 1024 + d * 32 + cf * 8);
        sts128(sb + OFF_WPHI + (hh >> 1) * 4096 + d * 128 + ((((hh & 1) * 4 + cf) ^ (d & 7)) << 4), v);
      }
      if (t < 56) {
        const uint4 v = ldg128_nc(b1 + 448 * j + t * 8);
        const uint32_t bw[4] = {v.x, v.y, v.z, v.w};
#pragma unroll
        for (int q = 0; q < 4; q++)
          asm volatile("st.shared.u32 [%0], %1;" ::"r"(sb + OFF_B1 + (q * 56 + t) * 4), "r"(mul_bf16x2(bw[q], 0x3f003f00u)) : "memory");
      }
      if (t < 16) {
        const uint4 v = ldg128_nc(b2 + 128 * j + t * 8);
        const uint32_t bw[4] = {v.x, v.y, v.z, v.w};
#pragma unroll
        for (int q = 0; q < 4; q++) asm volatile("st.shared.u32 [%0], %1;" ::"r"(sb + OFF_B2 + (q * 16 + t) * 4), "r"(mul_bf16x2(bw[q], 0x3f003f00u)) : "memory");
      }
      fence_proxy_async_smem();
      mbar_arrive(bars + B_MISC * 8);
      const bool hlead = (warp == 2) && elect_one();
      if (hlead) {
        mbar_wait(bars + B_EVCS * 8, 0); fence_gpu(); flag_add(&g_flags[(FL_CS + j) * 32]);
        flag_wait(&g_flags[(FL_CS + j) * 32], 16);
      }
      bar_sync(4, 64);
      {
        float4 a = make_float4(0.f, 0.f, 0.f, 0.f);
#pragma unroll
        for (int q = 0; q < 8; q++) { const float4 v = ldg128_cg(g_csp + (j * 8 + q) * 256 + 4 * t); a.x += v.x; a.y += v.y; a.z += v.z; a.w += v.w; }
        const uint32_t h0 = pack_bf16(a.x, a.y), h1 = pack_bf16(a.z, a.w);
        const uint32_t l0 = pack_bf16(a.x - lo_f(h0), a.y - hi_f(h0)), l1 = pack_bf16(a.z - lo_f(h1), a.w - hi_f(h1));
        mbar_wait(bars + B_EVLN * 8, 0);
#pragma unroll 4
        for (int q = 0; q < 16; q++) sts128(sb + OFF_TP + (q * 64 + t) * 16, make_uint4(0u, 0u, 0u, 0u));
        fence_proxy_async_smem();
        bar_sync(4, 64);
#pragma unroll
        for (int c = 0; c < 2; c++) {
          const uint32_t tb = sb + OFF_TP + c * 8192 + (t >> 4) * 2048 + (t & 1) * 8;
          asm volatile("st.shared.v2.u32 [%0], {%1, %2};" ::"r"(tb + (((t >> 1) & 7) << 4)), "r"(h0), "r"(h1) : "memory");
          asm volatile("st.shared.v2.u32 [%0], {%1, %2};" ::"r"(tb + 128 + ((((t >> 1) & 7) ^ 1) << 4)), "r"(l0), "r"(l1) : "memory");
        }
        fence_proxy_async_smem();
        mbar_arrive(bars + B_TAB * 8);
      }
      if (hlead) flag_wait(&g_flags[(FL_KV + j) * 32], 16);
      bar_sync(4, 64);
      {
        const int fr = t >> 3, ch = t & 7, p = m >> 3;
        const int hh = 2 * p + (ch >> 2), f = (m & 7) * 8 + fr;
        const float* hb_ = g_acc + (j * 4 + hh) * ACC_HEAD;
        const float* src = hb_ + (f >> 4) * 512 + (2 * (ch & 3) + ((f >> 3) & 1)) * 64 + (f & 7) * 8;
        const bool zt = (ch & 3) == 3;
        float a[8] = {0.f, 0.f, 0.f, 0.f, 0.f, 0.f, 0.f, 0.f}, z = 0.f;
#pragma unroll
        for (int c = 0; c < NCOPY; c++) {
          const float4 u = ldg128_cg(src + c * 32 * ACC_HEAD), v = ldg128_cg(src + c * 32 * ACC_HEAD + 4);
          float zc = 0.f;
          if (zt) asm volatile("ld.global.cg.f32 %0, [%1];" : "=f"(zc) : "l"(hb_ + c * 32 * ACC_HEAD + 2048 + f) : "memory");
          a[0] += u.x; a[1] += u.y; a[2] += u.z; a[3] += u.w; a[4] += v.x; a[5] += v.y; a[6] += v.z; a[7] += v.w; z += zc;
        }
        sts128(sb + OFF_TV + fr * 128 + ((ch ^ fr) << 4),
               make_uint4(pack_bf16(a[0], a[1]), pack_bf16(a[2], a[3]), pack_bf16(a[4], a[5]), pack_bf16(a[6], a[7])));
        if (zt) asm volatile("st.shared.u16 [%0], %1;" ::"r"(sb + OFF_TV + 1024 + (ch >> 2) * 16 + fr * 2), "h"((uint16_t)(pack_bf16(z, 0.f) & 0xffff)) : "memory");
        fence_proxy_async_smem();
        bar_sync(4, 64);
        if (hlead) {
          uint8_t* dst = g_kvt + j * 17408;
          bulk_store(dst + m * 1024, sb + OFF_TV, 1024);
          for (int h = 0; h < 2; h++) { const int zh = 2 * p + h; bulk_store(dst + 16384 + zh * 128 + (((m & 7) ^ zh) << 4), sb + OFF_TV + 1024 + h * 16, 16); }
          bulk_commit(); bulk_wait_all();
          fence_gpu(); flag_add(&g_flags[(FL_KV2 + j) * 32]);
          mbar_wait(bars + B_EV5 * 8, 0);
          tma_store_2d(&tm_px, sb + OFF_WPHI, 128 * (j ^ 1), m * 128);
          tma_store_2d(&tm_px, sb + OFF_WPHI + 16384, 128 * (j ^ 1) + 64, m * 128);
          bulk_commit(); bulk_wait_all();
          fence_gpu(); flag_add(&g_flags[(FL_PX + m * 8 + (j ^ 1)) * 32]);
          flag_wait(&g_flags[(FL_PX + m * 8 + j) * 32], 1);
          mbar_expect_tx(bars + B_PXT * 8, 32768);
          tma_load_2d(sb + OFF_WPHI, &tm_px, bars + B_PXT * 8, 128 * j, m * 128);
          tma_load_2d(sb + OFF_WPHI + 16384, &tm_px, bars + B_PXT * 8, 128 * j + 64, m * 128);
          mbar_wait(bars + B_EV6 * 8, 0);
          mbar_expect_tx(bars + B_XT * 8, 32768);
          tma_load_2d(sb + OFF_WPHI, &tm_x, bars + B_XT * 8, 128 * j, m * 128);
          tma_load_2d(sb + OFF_WPHI + 16384, &tm_x, bars + B_XT * 8, 128 * j + 64, m * 128);
          done_and_reset();
        }
      }
    }
  } else {
    reg_alloc<232>();
    const int cw = (warp >> 2) - 1, w = warp & 3;
    const uint32_t tid128 = threadIdx.x & 127;
    const int r0 = lane >> 2, q4 = lane & 3;
    const bool leader = elect_one();
    uint4 xv[8];
    const int lnrow = m * 128 + j * 16 + (warp - 4) * 2 + (lane >> 4);

    const uint32_t zero = lds32(sb + OFF_CST + 4);
    float acc[128];
    const uint32_t tileP = sb + OFF_TP + cw * 8192, tileV = sb + OFF_TV + cw * 4096;
    const int grow = m * 128 + cw * 64 + w * 16;
    const uint32_t lrow = (lane & 7) + ((lane >> 3) & 1) * 8;
    const uint32_t sw128 = (((lane >> 4) ^ (lane & 7)) << 4);
    const uint32_t sw64 = (((lane >> 4) ^ ((lrow >> 1) & 3)) << 4);
    uint32_t rbars;
    asm volatile("mapa.shared::cluster.u32 %0, %1, %2;" : "=r"(rbars) : "r"(bars), "r"(tid128 & 1));
    uint32_t alo = ((sd + cw * 8192) >> 4) | LBO_1, blo = ((sd + 16384) >> 4) | LBO_B, za = 0;
#define FRESH_BASES() do { asm volatile("add.u32 %0, %0, %2;\nadd.u32 %1, %1, %2;" : "+r"(alo), "+r"(blo) : "r"(zero)); } while (0)
#define ANCHOR() za = anchor(zero)
    mbar_probe_clear();
    constexpr int PP = 13;
#define TURN_WAIT() do { if ((PP >> PHASE) & 1) bar_sync(5 + cw, 256); } while (0)
#define TURN_PASS() do { if ((PP >> PHASE) & 1) bar_arrive(5 + (cw ^ 1), 256); } while (0)
    if (PP != 0 && cw == 1) bar_arrive(5, 256);
#define STEP1_ISSUE(N, S) \
    mbar_wait_probed(bars + (B_FULL1 + (S)) * 8, it & 1); \
    TURN_WAIT(); \
    wgmma_fence(); \
    issue_main<N>(acc, alo + (S) * (SLOT1 >> 4), blo + (S) * (SLOT1 >> 4), (S) > 0 || it > 0);
#define STEP1_DONE(S) \
    wgmma_commit(); \
    TURN_PASS(); \
    wgmma_wait<1>(); \
    ANCHOR(); \
    arrive_if(rbars + (B_EMPTY1 + (((S) + 3) & 3)) * 8, tid128, ((S) > 0 || it > 0) ? 2u : 0u); \
    mbar_probe(bars + (B_FULL1 + (((S) + 1) & 3)) * 8, ((S) < 3 ? it : it + 1) & 1); \
    FRESH_BASES();
#define TILE1_END(N) \
    wgmma_wait<0>(); \
    arrive_if(rbars + (B_EMPTY1 + 3) * 8, tid128, 2u); \
    fence_regs<(N) / 2>(acc);
#define STEP2_DONE(S, PAR, REL) \
    wgmma_commit(); \
    TURN_PASS(); \
    wgmma_wait<1>(); \
    ANCHOR(); \
    arrive_if(rbars + (B_EMPTY2 + (((S) + 5) % 6)) * 8, tid128, REL); \
    mbar_probe(bars + (B_FULL2 + (((S) + 1) % 6)) * 8, ((S) < 5 ? (PAR) : (PAR) + 1) & 1); \
    FRESH_BASES();

#define PHASE 0
    {
      const int it = 0;
      float cs[32];
      const uint32_t olo = ((sd + OFF_Z) >> 4) | LBO_1, cch = (2 * rank + cw) * (4096 >> 4);
#define COLSUM(S) \
      _Pragma("unroll") for (int kk = 0; kk < 4; kk++) { \
        const uint64_t da = dsc(olo, 1u << 30), db = dsc(blo + (S) * (SLOT1 >> 4) + cch + (((kk >> 1) * 16384 + (kk & 1) * 2048) >> 4), HI128); \
        if ((S) == 0 && kk == 0) wgmma_ss64_i<0, 1>(cs, da, db); else wgmma_ss64<0, 1>(cs, da, db); \
      }
      STEP1_ISSUE(256, 0) COLSUM(0) STEP1_DONE(0)
#pragma unroll
      for (int i = 0; i < 8; i++) xv[i] = ldg128_nc(x + (size_t)lnrow * D_ + (i * 16 + (lane & 15)) * 8);
      STEP1_ISSUE(256, 1) COLSUM(1) STEP1_DONE(1)
      STEP1_ISSUE(256, 2) STEP1_DONE(2)
      fence_regs<32>(cs);
      if (w == 0) {
        const uint32_t cst_ = sb + OFF_ZST + cw * 256;
        if (lane < 4) {
#pragma unroll
          for (int b = 0; b < 8; b++) asm volatile("st.shared.v2.f32 [%0], {%1, %2};" ::"r"(cst_ + b * 32 + lane * 8), "f"(cs[4 * b]), "f"(cs[4 * b + 1]) : "memory");
        }
        fence_proxy_async_smem();
        __syncwarp();
        if (leader) {
          bulk_store(g_csp + (j * 8 + (m >> 1)) * 256 + (2 * rank + cw) * 64, cst_, 256);
          bulk_commit();
        }
      }
      STEP1_ISSUE(256, 3) STEP1_DONE(3)
    }
    float mean, rs;
    uint32_t nm2;
    {
      float s = __uint_as_float(za);
#pragma unroll
      for (int i = 0; i < 8; i++) {
        const uint32_t u[4] = {xv[i].x, xv[i].y, xv[i].z, xv[i].w};
#pragma unroll
        for (int e = 0; e < 4; e++) s += lo_f(u[e]) + hi_f(u[e]);
      }
#pragma unroll
      for (int o = 8; o > 0; o >>= 1) s += __shfl_xor_sync(0xffffffffu, s, o);
      mean = s * (1.0f / 1024.0f);
      pinf<1>(&mean);
    }
    const uint32_t lstg = tileP + w * 2048;
    const int lnrow0 = m * 128 + j * 16 + (warp - 4) * 2;
#define LN_OUT(I0) \
      _Pragma("unroll") for (int i = (I0); i < (I0) + 4; i++) { \
        const uint32_t u[4] = {xv[i].x, xv[i].y, xv[i].z, xv[i].w}; \
        uint32_t o[4]; \
        _Pragma("unroll") for (int e = 0; e < 4; e++) { \
          const uint32_t dd = add_bf16x2(u[e], nm2 ^ za); \
          o[e] = pack_bf16(lo_f(dd) * rs, hi_f(dd) * rs); \
        } \
        sts128(lstg + (lane >> 4) * 1024 + (i - (I0)) * 256 + (lane & 15) * 16, make_uint4(o[0], o[1], o[2], o[3])); \
      } \
      fence_proxy_async_smem(); \
      __syncwarp(); \
      if (leader) { \
        bulk_store(g_xn + (size_t)lnrow0 * D_ + (I0) * 128, lstg, 1024); \
        bulk_store(g_xn + (size_t)(lnrow0 + 1) * D_ + (I0) * 128, lstg + 1024, 1024); \
        if ((I0) == 0) bulk_store(g_stats + lnrow0, sb + OFF_TV + 4096 + 1024 + (warp - 4) * 16, 16); \
        bulk_commit(); \
      }
    {
      const int it = 1;
      STEP1_ISSUE(256, 0) STEP1_DONE(0)
      {
        float ss = __uint_as_float(za);
#pragma unroll
        for (int i = 0; i < 8; i++) {
          const uint32_t u[4] = {xv[i].x, xv[i].y, xv[i].z, xv[i].w};
#pragma unroll
          for (int e = 0; e < 4; e++) { const float d0 = lo_f(u[e]) - mean, d1 = hi_f(u[e]) - mean; ss = fmaf(d0, d0, ss); ss = fmaf(d1, d1, ss); }
        }
#pragma unroll
        for (int o = 8; o > 0; o >>= 1) ss += __shfl_xor_sync(0xffffffffu, ss, o);
        nm2 = pack_bf16(-mean, -mean);
        const float sdv = bf16r(__fsqrt_rn(bf16r(bf16r(ss * (1.0f / 1024.0f)) + 1e-5f)));
        rs = __frcp_rn(sdv);
        if ((lane & 15) == 0)
          asm volatile("st.shared.v2.f32 [%0], {%1, %2};" ::"r"(sb + OFF_TV + 4096 + 1024 + (warp - 4) * 16 + (lane >> 4) * 8), "f"(-lo_f(nm2)), "f"(rs) : "memory");
      }
      STEP1_ISSUE(256, 1) STEP1_DONE(1)
      if (w == 0) if (leader) { bulk_wait_all(); mbar_arrive(bars + B_EVCS * 8); }
      LN_OUT(0)
      STEP1_ISSUE(256, 2) STEP1_DONE(2)
      if (leader) bulk_wait_read();
      __syncwarp();
      LN_OUT(4)
      STEP1_ISSUE(256, 3) STEP1_DONE(3)
    }
    {
      const int it = 2;
      STEP1_ISSUE(256, 0) STEP1_DONE(0)
      if (leader) { bulk_wait_all(); mbar_arrive(bars + B_EVLN * 8); }
      STEP1_ISSUE(256, 1) STEP1_DONE(1) STEP1_ISSUE(256, 2) STEP1_DONE(2) STEP1_ISSUE(256, 3) STEP1_DONE(3)
    }
    float rA, rB;
    {
      const int it = 3;
      STEP1_ISSUE(256, 0) STEP1_DONE(0) STEP1_ISSUE(256, 1) STEP1_DONE(1)
      mbar_wait(bars + B_TAB * 8, 0);
      float mA, mB;
      const uint32_t stt = tileV + (cw * 64 + w * 16 + r0) * 8;
      asm volatile("ld.shared.v2.f32 {%0, %1}, [%2];" : "=f"(mA), "=f"(rA) : "r"(stt));
      asm volatile("ld.shared.v2.f32 {%0, %1}, [%2];" : "=f"(mB), "=f"(rB) : "r"(stt + 64));
      uint32_t am[4] = {q4 == 0 ? pack_bf16(-mA, -mA) : 0u, q4 == 0 ? pack_bf16(-mB, -mB) : 0u, 0u, 0u};
      pin<4>(am);
      STEP1_ISSUE(256, 2) STEP1_DONE(2)
      STEP1_ISSUE(256, 3)
      wgmma_rs256<1>(acc, am, dsc(((sd + OFF_TP + cw * 8192) >> 4) | ((2048u >> 4) << 16), HI128));
      STEP1_DONE(3)
    }
    TILE1_END(256)
    uint32_t st[48];
#undef PHASE
#define PHASE 1
    {
      uint32_t k0[8], kq[24], vp[32];
#pragma unroll
      for (int i = 0; i < 8; i++) k0[i] = pack_bf16(acc[2 * i], acc[2 * i + 1]);
#pragma unroll
      for (int i = 0; i < 24; i++) kq[i] = pack_bf16(acc[16 + 2 * i], acc[16 + 2 * i + 1]);
#pragma unroll
      for (int i = 0; i < 32; i++) { const float r = (i & 1) ? rB : rA; vp[i] = pack_bf16(acc[64 + 2 * i] * r, acc[64 + 2 * i + 1] * r); }
      float pk[16], kvacc[20];
      mbar_wait(bars + B_MISC * 8, 0);
      wgmma_fence();
      issue_phi<false>(pk, k0, wphi_lo(sd, 0));
      wgmma_commit();
      const uint32_t plo = ((sd + OFF_TP + cw * 8192) >> 4) | LBO_1;
      const uint32_t vlo = ((sd + OFF_TV + cw * 4096) >> 4) | (((OFF_Z - OFF_TV - cw * 4096) >> 4) << 16);
      const uint32_t pa = tileP + (w * 16 + (lane & 7)) * 128 + (((lane >> 3) ^ (lane & 7)) << 4), va = tileV + (w * 16 + lrow) * 64 + sw64;
      const uint32_t kstg = tileP + w * 2048, zstg = sb + OFF_ZST + (cw * 4 + w) * 64;
      float* gacc = g_acc + (((m >> 1) % NCOPY) * 8 + j) * 4 * ACC_HEAD + w * 512;
      auto stage_kv = [&]() {
#pragma unroll
        for (int p = 0; p < 8; p++)
          asm volatile("st.shared.v2.f32 [%0], {%1, %2};" ::"r"(kstg + p * 256 + lane * 8), "f"(kvacc[2 * p]), "f"(kvacc[2 * p + 1]) : "memory");
        if (q4 == 0) {
          asm volatile("st.shared.f32 [%0], %1;" ::"r"(zstg + r0 * 4), "f"(kvacc[16]) : "memory");
          asm volatile("st.shared.f32 [%0], %1;" ::"r"(zstg + 32 + r0 * 4), "f"(kvacc[18]) : "memory");
        }
      };
      auto send_kv = [&](int hh) {
        fence_proxy_async_smem();
        __syncwarp();
        if (leader) {
          asm volatile("cp.reduce.async.bulk.global.shared::cta.bulk_group.add.f32 [%0], [%1], 2048;" ::"l"(gacc + hh * ACC_HEAD), "r"(kstg) : "memory");
          asm volatile("cp.reduce.async.bulk.global.shared::cta.bulk_group.add.f32 [%0], [%1], 64;" ::"l"(gacc + hh * ACC_HEAD + 2048 - w * 512 + w * 16), "r"(zstg) : "memory");
          bulk_commit();
        }
      };
#pragma unroll 1
      for (int it = 0; it < 4; it++) {
        uint32_t u[8], ph8[8];
        float M[4], e0[16], e1[16], s0[2], s1[2];
        STEP1_ISSUE(192, 0) STEP1_DONE(0)
        fence_regs<16>(pk);
        if (it > 0) {
          fence_regs<20>(kvacc);
          bar_sync(2 + cw, 128);
          stage_kv();
#pragma unroll
          for (int i = 0; i < 16; i++) kq[i] = kq[i + 8];
        }
        hh_part1<true>(pk, u, M, rA, rB);
        STEP1_ISSUE(192, 1) STEP1_DONE(1)
        if (it == 1) mbar_wait(bars + B_KVP * 8, 0);
        if (it > 0) send_kv(it - 1);
        stsm4(va, vp[0], vp[1], vp[2], vp[3]);
        stsm4x<32>(va, vp[4], vp[5], vp[6], vp[7]);
        hh_part2a<0>(u, M, e0, s0, za);
        STEP1_ISSUE(192, 2) STEP1_DONE(2)
        hh_sums(s0, za);
        hh_part2a<1>(u, M, e1, s1, za);
        hh_scale<0, true>(e0, s0, ph8);
        if (leader) bulk_wait_read();
        __syncwarp();
        stsm4(pa, ph8[0], ph8[1], ph8[2], ph8[3]);
        stsm4x<64>(pa, ph8[4], ph8[5], ph8[6], ph8[7]);
        STEP1_ISSUE(192, 3) STEP1_DONE(3)
        hh_sums(s1, za);
#pragma unroll
        for (int i = 0; i < 24; i++) vp[i] = vp[i + 8];
        hh_scale<1, true>(e1, s1, ph8);
        stsm4(pa + 1024, ph8[0], ph8[1], ph8[2], ph8[3]);
        stsm4x<64>(pa + 1024, ph8[4], ph8[5], ph8[6], ph8[7]);
        fence_proxy_async_smem();
        bar_sync(2 + cw, 128);
        wgmma_fence();
#pragma unroll
        for (int ks = 0; ks < 4; ks++) {
          const uint64_t da = dsc(plo + ks * (2048 >> 4), HI128);
          const uint64_t dv = dsc(vlo + ks * (1024 >> 4) - ((uint32_t)(ks * (1024 >> 4)) << 16), HI64);
          if (ks == 0) wgmma_ss40_z<1, 1>(kvacc, da, dv); else wgmma_ss40<1, 1>(kvacc, da, dv);
        }
        issue_phi<true>(pk, kq, wphi_lo(sd, it + 1));
        wgmma_commit();
      }
      TILE1_END(192)
      fence_regs<20>(kvacc);
      bar_sync(2 + cw, 128);
      stage_kv();
      send_kv(3);
    }
    const uint32_t hstg = tileP + w * 2048;
    const uint32_t b1a = sb + OFF_B1 + q4 * 224;
#undef PHASE
#define PHASE 2
    const uint32_t hstg_lane = hstg + lrow * 128 + sw128;
    {
      uint32_t hb[2], ba = b1a;
      lds64(hb, ba);
#pragma unroll 1
      for (int t = 0; t < 2; t++) {
#pragma unroll
        for (int i = 0; i < 48; i++) st[i] = pack_bf16(acc[2 * i], acc[2 * i + 1]);
#pragma unroll 1
        for (int it = 0; it < 4; it++) {
          STEP1_ISSUE(192, 0) STEP1_DONE(0)
          if (it > 0) {
            fence_proxy_async_smem();
            __syncwarp();
            if (leader) { tma_store_2d(&tm_hst, hstg, 448 * j + 192 * t + 64 * (it - 1), grow); bulk_commit(); }
          }
          if (it < 3) { gelu4<0>(st, hb, za); lds64(hb, ba + 8); }
          STEP1_ISSUE(192, 1) STEP1_DONE(1)
          if (it < 3) { gelu4<4>(st, hb, za); lds64(hb, ba + 16); }
          STEP1_ISSUE(192, 2) STEP1_DONE(2)
          if (it < 3) { gelu4<8>(st, hb, za); lds64(hb, ba + 24); }
          if (it == 0) if (leader) { bulk_wait_all(); mbar_arrive(bars + (B_EV + t) * 8); }
          STEP1_ISSUE(192, 3) STEP1_DONE(3)
          if (it < 3) {
            gelu4<12>(st, hb, za);
            ba += 32;
            lds64(hb, ba);
            if (leader) bulk_wait_read();
            __syncwarp();
            stsm4(hstg_lane, st[0], st[1], st[2], st[3]);
            stsm4x<32>(hstg_lane, st[4], st[5], st[6], st[7]);
            stsm4x<64>(hstg_lane, st[8], st[9], st[10], st[11]);
            stsm4x<96>(hstg_lane, st[12], st[13], st[14], st[15]);
#pragma unroll
            for (int i = 0; i < 32; i++) st[i] = st[i + 16];
          }
        }
        TILE1_END(192)
      }
    }
#pragma unroll
    for (int i = 0; i < 48; i++) st[i] = pack_bf16(acc[2 * i], acc[2 * i + 1]);

#undef PHASE
#define PHASE 3
    {
      const uint32_t ostg = tileV + w * 1024, ostg_lane = ostg + lrow * 64 + sw64;
      const uint32_t zlo = ((sd + OFF_Z) >> 4) | LBO_1;
      const uint32_t b6 = b1a + 48 * 4;
      float pq[16];
      uint32_t phi[16];
      {
        uint32_t hb[2], hc[2];
        lds64(hb, b6); lds64(hc, b6 + 8);
        const int it = 0;
        STEP1_ISSUE(256, 0) STEP1_DONE(0)
        gelu4<0>(st, hb, za); gelu4<4>(st, hc, za);
        lds64(hb, b6 + 16); lds64(hc, b6 + 24);
        if (leader) { bulk_wait_all(); mbar_arrive(bars + (B_EV + 2) * 8); }
        STEP1_ISSUE(256, 1)
        issue_phi<false>(pq, st + 16, wphi_lo(sd, 0));
        STEP1_DONE(1)
        gelu4<8>(st, hb, za); gelu4<12>(st, hc, za);
        if (leader) bulk_wait_read();
        __syncwarp();
        stsm4(hstg_lane, st[0], st[1], st[2], st[3]);
        stsm4x<32>(hstg_lane, st[4], st[5], st[6], st[7]);
        stsm4x<64>(hstg_lane, st[8], st[9], st[10], st[11]);
        stsm4x<96>(hstg_lane, st[12], st[13], st[14], st[15]);
      }
      float num[16], den[4];
#pragma unroll 1
      for (int i = 0; i < 5; i++) {
        float M[4], e[16], s0[2], s1[2];
        uint32_t u[8];
        {
          const int it = i;
          STEP1_ISSUE(256, 2) STEP1_DONE(2)
          fence_regs<16>(pq);
          if (i == 0) {
            fence_proxy_async_smem();
            __syncwarp();
            if (leader) { tma_store_2d(&tm_hst, hstg, 448 * j + 384, grow); bulk_commit(); }
          } else {
            fence_regs<16>(num); fence_regs<4>(den);
            const int hh = i - 1;
            const int src = (lane & ~3) | (hh >> 1);
            const float d0 = __shfl_sync(0xffffffffu, (hh & 1) ? den[1] : den[0], src), d1 = __shfl_sync(0xffffffffu, (hh & 1) ? den[3] : den[2], src);
            const float i0 = rcpf(bf16r(bf16r(d0) + 1e-6f)), i1 = rcpf(bf16r(bf16r(d1) + 1e-6f));
            uint32_t o[8];
#pragma unroll
            for (int b = 0; b < 4; b++) {
              const uint32_t n0 = pack_bf16(num[4 * b], num[4 * b + 1]), n1 = pack_bf16(num[4 * b + 2], num[4 * b + 3]);
              o[2 * b] = pack_bf16(lo_f(n0) * i0, hi_f(n0) * i0);
              o[2 * b + 1] = pack_bf16(lo_f(n1) * i1, hi_f(n1) * i1);
            }
            if (leader) bulk_wait_read();
            __syncwarp();
            stsm4(ostg_lane, o[0], o[1], o[2], o[3]);
            stsm4x<32>(ostg_lane, o[4], o[5], o[6], o[7]);
#pragma unroll
            for (int z = 24; z < 40; z++) st[z] = st[z + 8];
          }
          if (i < 4) hh_part1<false>(pq, u, M);
          STEP1_ISSUE(256, 3) STEP1_DONE(3)
          if (i == 0) if (leader) { bulk_wait_read(); mbar_arrive(bars + B_EVK * 8); }
          if (i == 4) {
            fence_proxy_async_smem();
            __syncwarp();
            if (leader) { tma_store_2d(&tm_ost, ostg, 128 * j + 96, grow); bulk_commit(); }
          }
          if (i < 4) {
            hh_part2a<0>(u, M, e, s0, za);
            hh_sums(s0, 0u);
            hh_scale<0, false>(e, s0, phi);
          }
        }
        {
          const int it = i + 1;
          STEP1_ISSUE(256, 0) STEP1_DONE(0)
          if (i < 4) {
            hh_part2a<1>(u, M, e, s1, za);
            hh_sums(s1, 0u);
            hh_scale<1, false>(e, s1, phi);
          }
          if (i == 0) mbar_wait(bars + B_KVT * 8, 0);
          STEP1_ISSUE(256, 1)
          {
            const uint32_t klo = ((sd + OFF_TP + ((i >> 1) & 1) * 8192 + (i & 1) * 64) >> 4) | LBO_1;
            wgmma_rs32_z<1>(num, phi, dsc(klo, HI128));
            wgmma_rs8_z<0>(den, phi, dsc(zlo, HI128));
#pragma unroll
            for (int kb = 1; kb < 4; kb++) {
              wgmma_rs32<1>(num, phi + 4 * kb, dsc(klo + kb * (2048 >> 4), HI128));
              wgmma_rs8<0>(den, phi + 4 * kb, dsc(zlo + kb * 2, HI128));
            }
            issue_phi<true>(pq, st + 24, wphi_lo(sd, i + 1));
          }
          STEP1_DONE(1)
          if (i == 0) {
            if (leader) { bulk_wait_all(); mbar_arrive(bars + (B_EV + 3) * 8); }
          } else if (i < 4) {
            fence_proxy_async_smem();
            __syncwarp();
            if (leader) { tma_store_2d(&tm_ost, ostg, 128 * j + 32 * (i - 1), grow); bulk_commit(); }
          }
        }
      }
      {
        const int it = 5;
        STEP1_ISSUE(256, 2) STEP1_DONE(2)
        if (leader) { bulk_wait_all(); mbar_arrive(bars + (B_EV + 4) * 8); }
        STEP1_ISSUE(256, 3) STEP1_DONE(3)
      }
      TILE1_END(256)
    }
#undef PHASE
#define PHASE 4
    float sacc[64];
    uint32_t gp[32];
#pragma unroll
    for (int i = 0; i < 32; i++) gp[i] = pack_bf16(acc[64 + 2 * i], acc[64 + 2 * i + 1]);
    mbar_probe_clear();
    {
      const uint32_t xstg = sb + OFF_WPHI + (cw * 64 + w * 16) * 128, xstg_lane = xstg + lrow * 128 + sw128;
      uint32_t bias[16];
      mbar_wait(bars + (B_EV + 4) * 8, 0);
#pragma unroll
      for (int c = 0; c < 2; c++) {
        stsm4(xstg_lane + c * 16384, gp[16 * c], gp[16 * c + 1], gp[16 * c + 2], gp[16 * c + 3]);
        stsm4x<32>(xstg_lane + c * 16384, gp[16 * c + 4], gp[16 * c + 5], gp[16 * c + 6], gp[16 * c + 7]);
        stsm4x<64>(xstg_lane + c * 16384, gp[16 * c + 8], gp[16 * c + 9], gp[16 * c + 10], gp[16 * c + 11]);
        stsm4x<96>(xstg_lane + c * 16384, gp[16 * c + 12], gp[16 * c + 13], gp[16 * c + 14], gp[16 * c + 15]);
      }
      fence_proxy_async_smem();
      __syncwarp();
      if (lane == 0) mbar_arrive(bars + B_EV5 * 8);
#define R2_STEP(K, A, SD) \
      mbar_wait_probed(bars + (B_FULL2 + (K) % 6) * 8, ((K) / 6) & 1); \
      TURN_WAIT(); \
      wgmma_fence(); \
      issue_main<128>(A, alo + ((K) % 6) * (SLOT2 >> 4), blo + ((K) % 6) * (SLOT2 >> 4), SD); \
      STEP2_DONE((K) % 6, ((K) / 6) & 1, (K) > 0 ? 2u : 0u)
#define SILU(I0, I1) \
      _Pragma("unroll") for (int i = (I0); i < (I1); i++) { \
        uint32_t h2; \
        asm("fma.rn.bf16x2 %0, %1, %2, %3;" : "=r"(h2) : "r"(pack_bf16(acc[2 * i] + lo_f(gp[i]), acc[2 * i + 1] + hi_fa(gp[i], za))), "r"(0x3f003f00u ^ za), "r"(bias[i >> 1])); \
        const float h0 = lo_f(h2), h1 = hi_f(h2); \
        gp[i] = pack_bf16(fmaf(h0, tanhf_a(h0), h0), fmaf(h1, tanhf_a(h1), h1)); \
      } \
      pin<(I1) - (I0)>(gp + (I0));
      R2_STEP(0, acc, 1) R2_STEP(1, acc, 1) R2_STEP(2, acc, 1) R2_STEP(3, acc, 1)
      R2_STEP(4, acc, 1) R2_STEP(5, acc, 1) R2_STEP(6, acc, 1) R2_STEP(7, acc, 1)
      R2_STEP(8, sacc, 0)
      fence_regs<64>(acc);
#pragma unroll
      for (int q = 0; q < 4; q++)
        asm volatile("ld.shared.v4.u32 {%0, %1, %2, %3}, [%4];" : "=r"(bias[4 * q]), "=r"(bias[4 * q + 1]), "=r"(bias[4 * q + 2]), "=r"(bias[4 * q + 3]) : "r"(sb + OFF_B2 + q4 * 64 + q * 16));
      R2_STEP(9, sacc, 1) R2_STEP(10, sacc, 1) R2_STEP(11, sacc, 1) R2_STEP(12, sacc, 1)
      mbar_wait(bars + B_PXT * 8, 0);
#pragma unroll
      for (int c = 0; c < 2; c++)
#pragma unroll
        for (int p = 0; p < 4; p++)
          asm volatile("ldmatrix.sync.aligned.m8n8.x4.shared.b16 {%0, %1, %2, %3}, [%4];"
                       : "=r"(gp[16 * c + 4 * p]), "=r"(gp[16 * c + 4 * p + 1]), "=r"(gp[16 * c + 4 * p + 2]), "=r"(gp[16 * c + 4 * p + 3])
                       : "r"((xstg_lane + c * 16384) ^ (p << 5)) : "memory");
      {
        uint32_t dep = 0;
#pragma unroll
        for (int q = 0; q < 8; q++) dep |= gp[4 * q];
        dep = __reduce_or_sync(0xffffffffu, dep) & zero;
        if (lane == 0) mbar_arrive(bars + B_EV6 * 8 + dep);
      }
      R2_STEP(13, sacc, 1) SILU(0, 4)
      R2_STEP(14, sacc, 1) SILU(4, 7)
      R2_STEP(15, sacc, 1) SILU(7, 10)
      R2_STEP(16, sacc, 1) SILU(10, 13)
      R2_STEP(17, sacc, 1) SILU(13, 16)
      R2_STEP(18, sacc, 1) SILU(16, 19)
      R2_STEP(19, sacc, 1) SILU(19, 22)
      R2_STEP(20, sacc, 1) SILU(22, 25)
      R2_STEP(21, sacc, 1) SILU(25, 28)
      R2_STEP(22, sacc, 1) SILU(28, 32)
      R2_STEP(23, sacc, 1)
      wgmma_wait<0>();
      arrive_if(rbars + (B_EMPTY2 + (23 % 6)) * 8, tid128, 2u);
      fence_regs<64>(sacc);
    }
    {
      mbar_wait(bars + B_XT * 8, 0);
      const uint32_t stg = sb + OFF_WPHI + (cw * 64 + w * 16) * 128;
#pragma unroll
      for (int c = 0; c < 2; c++) {
#pragma unroll
        for (int p = 0; p < 4; p++) {
          const uint32_t ad = (stg + c * 16384 + lrow * 128 + sw128) ^ (p << 5);
          uint32_t xr[4], o[4];
          asm volatile("ldmatrix.sync.aligned.m8n8.x4.shared.b16 {%0, %1, %2, %3}, [%4];" : "=r"(xr[0]), "=r"(xr[1]), "=r"(xr[2]), "=r"(xr[3]) : "r"(ad) : "memory");
#pragma unroll
          for (int e = 0; e < 4; e++) {
            const int i = 16 * c + 4 * p + e;
            o[e] = add_bf16x2(xr[e], mul_bf16x2(pack_bf16(sacc[2 * i], sacc[2 * i + 1]), gp[i]));
          }
          stsm4(ad, o[0], o[1], o[2], o[3]);
        }
        fence_proxy_async_smem();
        __syncwarp();
        if (leader) { tma_store_2d(&tm_out, stg + c * 16384, 128 * j + 64 * c, grow); bulk_commit(); }
      }
      if (leader) bulk_wait_read();
    }
  }
}

typedef CUresult (*EncodeFn)(CUtensorMap*, CUtensorMapDataType, cuuint32_t, void*, const cuuint64_t*, const cuuint64_t*, const cuuint32_t*,
                             const cuuint32_t*, CUtensorMapInterleave, CUtensorMapSwizzle, CUtensorMapL2promotion, CUtensorMapFloatOOBfill);

CUtensorMap make_map(EncodeFn enc, const void* ptr, int rank, const cuuint64_t* dims, const cuuint64_t* strides, const cuuint32_t* box, CUtensorMapSwizzle sw) {
  CUtensorMap m;
  const cuuint32_t es[3] = {1, 1, 1};
  enc(&m, CU_TENSOR_MAP_DATA_TYPE_BFLOAT16, rank, const_cast<void*>(ptr), dims, strides, box, es, CU_TENSOR_MAP_INTERLEAVE_NONE, sw,
      CU_TENSOR_MAP_L2_PROMOTION_L2_128B, CU_TENSOR_MAP_FLOAT_OOB_FILL_NONE);
  return m;
}
CUtensorMap map2d(EncodeFn enc, const void* ptr, int rows, int cols, int boxc, int boxr, CUtensorMapSwizzle sw) {
  const cuuint64_t d[2] = {(cuuint64_t)cols, (cuuint64_t)rows}; const cuuint64_t s[1] = {(cuuint64_t)cols * 2};
  const cuuint32_t b[2] = {(cuuint32_t)boxc, (cuuint32_t)boxr};
  return make_map(enc, ptr, 2, d, s, b, sw);
}
CUtensorMap mapw(EncodeFn enc, const void* ptr, int rows, int cols, int nch) {
  const cuuint64_t d[3] = {64, (cuuint64_t)rows, (cuuint64_t)cols / 64}; const cuuint64_t s[2] = {(cuuint64_t)cols * 2, 128};
  const cuuint32_t b[3] = {64, 32, (cuuint32_t)nch};
  return make_map(enc, ptr, 3, d, s, b, CU_TENSOR_MAP_SWIZZLE_128B);
}

}

extern "C" void kernel_launch(void* const* d_in, const int* in_sizes, int n_in, void* d_out, int out_size) {
  const bf16* x = (const bf16*)d_in[0];
  const bf16* wqkv = (const bf16*)d_in[1];
  const bf16* wphi = (const bf16*)d_in[2];
  const bf16* wo = (const bf16*)d_in[3];
  const bf16* w1 = (const bf16*)d_in[5];
  const bf16* b1 = (const bf16*)d_in[6];
  const bf16* w2 = (const bf16*)d_in[7];
  const bf16* b2 = (const bf16*)d_in[8];
  static EncodeFn enc = nullptr;
  static void *p_xn = nullptr, *p_h = nullptr, *p_o = nullptr, *p_px = nullptr;
  if (!enc) {
    void* fn = nullptr; cudaDriverEntryPointQueryResult qr;
    cudaGetDriverEntryPoint("cuTensorMapEncodeTiled", &fn, cudaEnableDefault, &qr);
    enc = (EncodeFn)fn;
    cudaGetSymbolAddress(&p_xn, g_xn); cudaGetSymbolAddress(&p_h, g_h); cudaGetSymbolAddress(&p_o, g_o); cudaGetSymbolAddress(&p_px, g_px);
    cudaFuncSetAttribute(fused_kernel, cudaFuncAttributeMaxDynamicSharedMemorySize, SMEM_BYTES);
  }
  const CUtensorMap tm_xn = map2d(enc, p_xn, S_, D_, 64, 128, CU_TENSOR_MAP_SWIZZLE_128B);
  const CUtensorMap tm_h = map2d(enc, p_h, S_, F_, 64, 128, CU_TENSOR_MAP_SWIZZLE_128B);
  const CUtensorMap tm_o = map2d(enc, p_o, S_, D_, 64, 128, CU_TENSOR_MAP_SWIZZLE_128B);
  const CUtensorMap tm_wqkv = mapw(enc, wqkv, D_, 3 * D_, 2);
  const CUtensorMap tm_w1a = mapw(enc, w1, D_, F_, 3);
  const CUtensorMap tm_w1b = mapw(enc, w1, D_, F_, 1);
  const CUtensorMap tm_w2 = mapw(enc, w2, F_, D_, 2);
  const CUtensorMap tm_wo = mapw(enc, wo, D_, D_, 2);
  const CUtensorMap tm_hst = map2d(enc, p_h, S_, F_, 64, 16, CU_TENSOR_MAP_SWIZZLE_128B);
  const CUtensorMap tm_x = map2d(enc, x, S_, D_, 64, 128, CU_TENSOR_MAP_SWIZZLE_128B);
  const CUtensorMap tm_ost = map2d(enc, p_o, S_, D_, 32, 16, CU_TENSOR_MAP_SWIZZLE_64B);
  const CUtensorMap tm_out = map2d(enc, d_out, S_, D_, 64, 16, CU_TENSOR_MAP_SWIZZLE_128B);
  const CUtensorMap tm_px = map2d(enc, p_px, S_, D_, 64, 128, CU_TENSOR_MAP_SWIZZLE_128B);
  fused_kernel<<<128, 384, SMEM_BYTES>>>(tm_xn, tm_h, tm_o, tm_wqkv, tm_w1a, tm_w1b, tm_w2, tm_wo, tm_hst, tm_x, tm_ost, tm_out, tm_px, x, wphi, b1, b2);
}
```
